```python
import torch

def _softmax(x, axis=-1):
    return torch.softmax(x, dim=axis)
def _gelu(x):
    return torch.nn.functional.gelu(x, approximate="tanh")
def _silu(x):
    return torch.nn.functional.silu(x)
def _sigmoid(x):
    return torch.sigmoid(x)
def _layernorm(x, axis=-1, eps=1e-5):
    m = x.mean(dim=axis, keepdim=True)
    v = x.var(dim=axis, keepdim=True, unbiased=False)
    return (x - m) / torch.sqrt(v + eps)
def _scatter_add(tgt, idx, src, axis=0):
    return tgt.clone().index_add_(axis, idx, src)
def _segment_sum(src, seg, n):
    out = torch.zeros((n,) + src.shape[1:], dtype=src.dtype)
    return out.index_add_(0, seg, src)
def _pad(x, pw):
    flat = tuple(v for pair in reversed(pw) for v in pair)
    return torch.nn.functional.pad(x, flat)

kernel_name = 'gated_mix__ssm_conv_h3__geglu_ffn__prompt'

def setup_inputs():

    _w = (lambda a: (lambda t: t.to(torch.bfloat16) if t.is_floating_point() else t)(torch.as_tensor(a)))
    def _A_setup():
        B, S, D = 1, 2048, 512
        ks = 4
        return {
            "q": _w((lambda *s: torch.randn(*s, dtype=torch.bfloat16) * 0.05)(B, S, D)),
            "k": _w((lambda *s: torch.randn(*s, dtype=torch.bfloat16) * 0.2)(B, S, D)),
            "v": _w((lambda *s: torch.randn(*s, dtype=torch.bfloat16) * 0.2)(B, S, D)),
            "shift_k": _w((lambda *s: torch.randn(*s, dtype=torch.bfloat16) * 0.2)(D, ks) * 0.5),
            "ssm_k": _w((lambda *s: torch.randn(*s, dtype=torch.bfloat16) * 0.8)(D, S) * (1.0 / S ** 0.5)),
            "ssm_D": _w((lambda *s: torch.randn(*s, dtype=torch.bfloat16) * 0.2)(D)),
        }
    _A_in = _A_setup()

    def _B_setup():
        B, S, D, F = 1, 2048, 512, 1792
        return {
            "x": _w((lambda *s: torch.randn(*s, dtype=torch.bfloat16) * 0.05)(B, S, D)),
            "w_gate": _w((lambda *s: torch.randn(*s, dtype=torch.bfloat16) * 0.05)(D, F)),
            "w_up": _w((lambda *s: torch.randn(*s, dtype=torch.bfloat16) * 0.05)(D, F)),
            "w_down": _w((lambda *s: torch.randn(*s, dtype=torch.bfloat16) * 0.05)(F, D)),
        }
    _B_in = _B_setup()

    return {
        "A_q": _A_in["q"],
        "A_k": _A_in["k"],
        "A_v": _A_in["v"],
        "A_shift_k": _A_in["shift_k"],
        "A_ssm_k": _A_in["ssm_k"],
        "A_ssm_D": _A_in["ssm_D"],
        "B_x": _B_in["x"],
        "B_w_gate": _B_in["w_gate"],
        "B_w_up": _B_in["w_up"],
        "B_w_down": _B_in["w_down"],
        "gate_w": _w((lambda *s: torch.randn(*s, dtype=torch.bfloat16) * 0.05)(512) * 16.0),
    }

def reference(A_q, A_k, A_v, A_shift_k, A_ssm_k, A_ssm_D, B_x, B_w_gate, B_w_up, B_w_down, gate_w):
    def _A_ref(q, k, v, shift_k, ssm_k, ssm_D):
        B, S, D = q.shape
        ks = shift_k.shape[-1]
        k_pad = _pad(k, ((0, 0), (ks - 1, 0), (0, 0)))
        k_shift = torch.zeros_like(k)
        for t in range(ks):
            k_shift = k_shift + k_pad[:, t:t + S, :] * shift_k[:, ks - 1 - t][None, None, :]
        kv = k_shift * v
        L = 2 * S
        kv_pad = _pad(kv, ((0, 0), (0, S), (0, 0)))
        kf_pad = _pad(ssm_k, ((0, 0), (0, S)))
        kv_f = (lambda x, axes=(-2,-1): torch.fft.rfft2(x.float(), dim=axes))(kv_pad[:, None, :, :], axes=(1, 2))
        kf_f = (lambda x, axes=(-2,-1): torch.fft.rfft2(x.float(), dim=axes))(kf_pad[:, None, :], axes=(1, 2))
        kf_f = (lambda x, *d: x.permute(*d))(kf_f, 1, 2, 0)
        y_f = kv_f * kf_f[None, :, :, :]
        y = (lambda x, s, axes=(-2,-1): torch.fft.irfft2(x, s=s, dim=axes).to(torch.bfloat16))(y_f, (1, L), axes=(1, 2))[:, 0, :S, :]
        y = y + kv * ssm_D[None, None, :]
        return q * y

    def _B_ref(x, w_gate, w_up, w_down):
        return (_gelu(x @ w_gate) * (x @ w_up)) @ w_down

    x = A_q
    g = _sigmoid((x * gate_w).sum(-1, keepdims=True))
    a = _A_ref(x, A_k, A_v, A_shift_k, A_ssm_k, A_ssm_D)
    b = _B_ref(x, B_w_gate, B_w_up, B_w_down)
    return g * a + (1 - g) * b
```

```cpp
#include <cuda_runtime.h>
#include <cuda_bf16.h>
#include <cuda.h>
#include <stdint.h>

namespace {

constexpr int S_LEN = 2048, D_DIM = 512, F_DIM = 1792;
constexpr int NCTA = 128;
constexpr int NTHREADS = 512;
constexpr uint32_t SLOT = 16384;
constexpr uint32_t OFF_BAR = 14 * SLOT;
constexpr int B_XFULL = 0, B_XEMPTY = 8, B_WFULL = 16, B_WEMPTY = 22, B_WLAST = 28, B_GFULL = 34, B_GEMPTY = 41,
              B_QFULL = 48, B_CFULL = 49;
constexpr uint32_t OFF_GATE = OFF_BAR + 512;
constexpr uint32_t SMEM_USED = OFF_GATE + 512;
constexpr uint32_t SMEM_BYTES = SMEM_USED + 1024;
constexpr uint32_t CV_BASE = 8 * SLOT;
constexpr uint32_t CV_U = CV_BASE;
constexpr uint32_t CV_UCH = 5888, CV_UHALF = 2944;
constexpr uint32_t CV_H = CV_BASE + 11776;
constexpr uint32_t CV_HCOPY = 4160;
constexpr uint32_t CV_HRAW = CV_BASE + 20096;
constexpr uint32_t CV_P = CV_BASE + 24320;
constexpr int GRING = 7;
constexpr uint32_t SPIN_LIMIT = 1u << 24;

constexpr int C_DONE = 0, C_PRE = 1, C_CONV = 2, C_FH = 10, NCNT = 10 + 64;

__device__ __nv_bfloat16 g_H[(size_t)S_LEN * F_DIM];
__device__ uint4 g_u[D_DIM * 256];
__device__ __nv_bfloat16 g_yT[(size_t)D_DIM * S_LEN];
__device__ float g_gate[S_LEN];
__device__ unsigned g_cnt[NCNT * 32];

#define DBG(bit) 0
#define PROF(i) do {} while (0)
#define PROFG(i) do {} while (0)
#define PROFX(i, en) do {} while (0)

struct Maps {
  CUtensorMap x, wg0, wu0, wg1, wu1, h, wd, y, xq;
};

__device__ __forceinline__ uint32_t s2u(const void* p) { return (uint32_t)__cvta_generic_to_shared(p); }
__device__ __forceinline__ void mbar_init(uint32_t b, int c) {
  asm volatile("mbarrier.init.shared::cta.b64 [%0], %1;" ::"r"(b), "r"(c) : "memory");
}
__device__ __forceinline__ void mbar_expect(uint32_t b, uint32_t bytes) {
  asm volatile("mbarrier.arrive.expect_tx.shared::cta.b64 _, [%0], %1;" ::"r"(b), "r"(bytes) : "memory");
}
__device__ __forceinline__ void mbar_wait(uint32_t bar, uint32_t parity) {
  uint32_t done, it = 0;
  while (true) {
    asm volatile("{\n.reg .pred p;\nmbarrier.try_wait.parity.shared::cta.b64 p, [%1], %2;\nselp.u32 %0, 1, 0, p;\n}"
                 : "=r"(done) : "r"(bar), "r"(parity) : "memory");
    if (done) break;
    if (++it > SPIN_LIMIT) __trap();
  }
}
__device__ __forceinline__ void mbar_arrive_both(uint32_t bar) {
  asm volatile(
      "{\n.reg .b32 r0, r1;\n"
      "mapa.shared::cluster.u32 r0, %0, 0;\n"
      "mapa.shared::cluster.u32 r1, %0, 1;\n"
      "mbarrier.arrive.shared::cluster.b64 _, [r0];\n"
      "mbarrier.arrive.shared::cluster.b64 _, [r1];\n}" ::"r"(bar) : "memory");
}
__device__ __forceinline__ void tma2d(uint32_t dst, const CUtensorMap* m, int c0, int c1, uint32_t bar) {
  asm volatile("cp.async.bulk.tensor.2d.shared::cluster.global.mbarrier::complete_tx::bytes [%0], [%1, {%3, %4}], [%2];"
               ::"r"(dst), "l"(m), "r"(bar), "r"(c0), "r"(c1) : "memory");
}
__device__ __forceinline__ void tma2d_mc(uint32_t dst, const CUtensorMap* m, int c0, int c1, uint32_t bar) {
  asm volatile("cp.async.bulk.tensor.2d.shared::cluster.global.mbarrier::complete_tx::bytes.multicast::cluster [%0], [%1, {%3, %4}], [%2], %5;"
               ::"r"(dst), "l"(m), "r"(bar), "r"(c0), "r"(c1), "h"((uint16_t)3) : "memory");
}
__device__ __forceinline__ void tma3d_mc(uint32_t dst, const CUtensorMap* m, int c0, int c1, int c2, uint32_t bar) {
  asm volatile("cp.async.bulk.tensor.3d.shared::cluster.global.mbarrier::complete_tx::bytes.multicast::cluster [%0], [%1, {%3, %4, %5}], [%2], %6;"
               ::"r"(dst), "l"(m), "r"(bar), "r"(c0), "r"(c1), "r"(c2), "h"((uint16_t)3) : "memory");
}
__device__ __forceinline__ void bulk_g2s(uint32_t dst, const void* src, uint32_t bytes, uint32_t bar) {
  asm volatile("cp.async.bulk.shared::cluster.global.mbarrier::complete_tx::bytes [%0], [%1], %2, [%3];"
               ::"r"(dst), "l"(src), "r"(bytes), "r"(bar) : "memory");
}
__device__ __forceinline__ void prefetch_map(const CUtensorMap* m) {
  asm volatile("prefetch.tensormap [%0];" ::"l"(m) : "memory");
}
__device__ __forceinline__ void fence_proxy_async() { asm volatile("fence.proxy.async.global;" ::: "memory"); }
__device__ __forceinline__ void fence_proxy_smem() { asm volatile("fence.proxy.async.shared::cta;" ::: "memory"); }
__device__ __forceinline__ void wg_fence() { asm volatile("wgmma.fence.sync.aligned;" ::: "memory"); }
__device__ __forceinline__ void wg_commit() { asm volatile("wgmma.commit_group.sync.aligned;" ::: "memory"); }
template <int N> __device__ __forceinline__ void wg_wait() { asm volatile("wgmma.wait_group.sync.aligned %0;" ::"n"(N) : "memory"); }
__device__ __forceinline__ void bar_sync(int id, int n) { asm volatile("bar.sync %0, %1;" ::"r"(id), "r"(n) : "memory"); }
__device__ __forceinline__ void cluster_sync() {
  asm volatile("barrier.cluster.arrive.relaxed.aligned;\nbarrier.cluster.wait.aligned;" ::: "memory");
}
constexpr uint32_t SB0 = 1024;
__host__ __device__ constexpr uint32_t desc_lo(uint32_t off, uint32_t lbo) { return ((SB0 + off) >> 4) | ((lbo >> 4) << 16); }
__host__ __device__ constexpr uint32_t desc_hi(uint32_t sbo, uint32_t sw) { return (sbo >> 4) | (sw << 30); }
constexpr uint32_t HI_SW128 = desc_hi(1024, 1), HI_SW64 = desc_hi(512, 2), HI_NONE = desc_hi(128, 0);
__device__ __forceinline__ unsigned ld_acquire(const unsigned* p) {
  unsigned v;
  asm volatile("ld.acquire.gpu.global.u32 %0, [%1];" : "=r"(v) : "l"(p) : "memory");
  return v;
}
__device__ __forceinline__ void flag_wait(int idx, unsigned target) {
  const unsigned* p = &g_cnt[idx * 32];
  uint32_t it = 0;
  while ((int)(ld_acquire(p) - target) < 0) {
    if (++it > SPIN_LIMIT) __trap();
    __nanosleep(32);
  }
}
__device__ __forceinline__ void flag_signal(int idx) {
  asm volatile("red.release.gpu.global.add.u32 [%0], 1;" ::"l"(&g_cnt[idx * 32]) : "memory");
}
__device__ __forceinline__ unsigned read_epoch() {
  unsigned v;
  asm volatile("ld.relaxed.gpu.global.u32 %0, [%1];" : "=r"(v) : "l"(&g_cnt[C_DONE * 32]) : "memory");
  return v / NCTA + 1;
}
__device__ __forceinline__ uint32_t prmt(uint32_t a, uint32_t b, uint32_t s) { return __byte_perm(a, b, s); }
__device__ __forceinline__ uint32_t pack_bf16(float lo, float hi) {
  uint32_t r;
  asm("cvt.rn.bf16x2.f32 %0, %1, %2;" : "=r"(r) : "f"(hi), "f"(lo));
  return r;
}
__device__ __forceinline__ uint32_t bmul2(uint32_t a, uint32_t b) {
  uint32_t r;
  asm("mul.rn.bf16x2 %0, %1, %2;" : "=r"(r) : "r"(a), "r"(b));
  return r;
}
__device__ __forceinline__ uint32_t badd2(uint32_t a, uint32_t b) {
  uint32_t r;
  asm("add.rn.bf16x2 %0, %1, %2;" : "=r"(r) : "r"(a), "r"(b));
  return r;
}
__device__ __forceinline__ float bf_lo(uint32_t v) { return __uint_as_float(v << 16); }
__device__ __forceinline__ float bf_hi(uint32_t v) { return __uint_as_float(v & 0xFFFF0000u); }
__device__ __forceinline__ float bf_round(float f) { return __bfloat162float(__float2bfloat16_rn(f)); }
__device__ __forceinline__ uint32_t ldg32(const void* p) {
  uint32_t v;
  asm volatile("ld.global.nc.L1::no_allocate.b32 %0, [%1];" : "=r"(v) : "l"(p));
  return v;
}
__device__ __forceinline__ uint32_t ldg16(const void* p) {
  uint16_t v;
  asm volatile("ld.global.nc.L1::no_allocate.b16 %0, [%1];" : "=h"(v) : "l"(p));
  return v;
}
__device__ __forceinline__ uint4 ldg128(const void* p) {
  uint4 v;
  asm volatile("ld.global.nc.L1::no_allocate.v4.b32 {%0,%1,%2,%3}, [%4];" : "=r"(v.x), "=r"(v.y), "=r"(v.z), "=r"(v.w) : "l"(p));
  return v;
}
__device__ __forceinline__ uint32_t lds32(uint32_t a) {
  uint32_t v;
  asm volatile("ld.shared.b32 %0, [%1];" : "=r"(v) : "r"(a) : "memory");
  return v;
}
__device__ __forceinline__ uint4 lds128(uint32_t a) {
  uint4 v;
  asm volatile("ld.shared.v4.b32 {%0,%1,%2,%3}, [%4];" : "=r"(v.x), "=r"(v.y), "=r"(v.z), "=r"(v.w) : "r"(a) : "memory");
  return v;
}
__device__ __forceinline__ void sts32(uint32_t a, uint32_t v) { asm volatile("st.shared.b32 [%0], %1;" ::"r"(a), "r"(v) : "memory"); }
__device__ __forceinline__ void sts128(uint32_t a, uint32_t x, uint32_t y, uint32_t z, uint32_t w) {
  asm volatile("st.shared.v4.b32 [%0], {%1,%2,%3,%4};" ::"r"(a), "r"(x), "r"(y), "r"(z), "r"(w) : "memory");
}
__device__ __forceinline__ void ldsm4(uint32_t a, uint32_t& r0, uint32_t& r1, uint32_t& r2, uint32_t& r3) {
  asm volatile("ldmatrix.sync.aligned.m8n8.x4.shared.b16 {%0,%1,%2,%3}, [%4];" : "=r"(r0), "=r"(r1), "=r"(r2), "=r"(r3) : "r"(a) : "memory");
}
__device__ __forceinline__ void ldsm4t(uint32_t a, uint32_t& r0, uint32_t& r1, uint32_t& r2, uint32_t& r3) {
  asm volatile("ldmatrix.sync.aligned.m8n8.x4.trans.shared.b16 {%0,%1,%2,%3}, [%4];" : "=r"(r0), "=r"(r1), "=r"(r2), "=r"(r3) : "r"(a) : "memory");
}
__device__ __forceinline__ float tanh_approx(float x) {
  float r;
  asm("tanh.approx.f32 %0, %1;" : "=f"(r) : "f"(x));
  return r;
}
__device__ __forceinline__ float geglu(float g, float u) {
  float t = g * fmaf(g * g, 0.0356774081f, 0.7978845608f);
  float hx = 0.5f * g * u;
  return fmaf(hx, tanh_approx(t), hx);
}

__device__ __forceinline__ void wgmma_ss_n128(float (&d)[64], uint32_t alo, uint32_t ahi, uint32_t blo, uint32_t bhi, int sd) {
  asm volatile("{\n.reg .pred p;\n.reg .b64 da, db;\nsetp.ne.b32 p, %68, 0;\nmov.b64 da, {%64, %65};\nmov.b64 db, {%66, %67};\n"
    "wgmma.mma_async.sync.aligned.m64n128k16.f32.bf16.bf16 {%0,%1,%2,%3,%4,%5,%6,%7,%8,%9,%10,%11,%12,%13,%14,%15,%16,%17,%18,%19,%20,%21,%22,%23,%24,%25,%26,%27,%28,%29,%30,%31,%32,%33,%34,%35,%36,%37,%38,%39,%40,%41,%42,%43,%44,%45,%46,%47,%48,%49,%50,%51,%52,%53,%54,%55,%56,%57,%58,%59,%60,%61,%62,%63}, da, db, p, 1, 1, 0, 1;\n}"
    : "+f"(d[0]),"+f"(d[1]),"+f"(d[2]),"+f"(d[3]),"+f"(d[4]),"+f"(d[5]),"+f"(d[6]),"+f"(d[7]),"+f"(d[8]),"+f"(d[9]),"+f"(d[10]),"+f"(d[11]),"+f"(d[12]),"+f"(d[13]),"+f"(d[14]),"+f"(d[15]),"+f"(d[16]),"+f"(d[17]),"+f"(d[18]),"+f"(d[19]),"+f"(d[20]),"+f"(d[21]),"+f"(d[22]),"+f"(d[23]),"+f"(d[24]),"+f"(d[25]),"+f"(d[26]),"+f"(d[27]),"+f"(d[28]),"+f"(d[29]),"+f"(d[30]),"+f"(d[31]),"+f"(d[32]),"+f"(d[33]),"+f"(d[34]),"+f"(d[35]),"+f"(d[36]),"+f"(d[37]),"+f"(d[38]),"+f"(d[39]),"+f"(d[40]),"+f"(d[41]),"+f"(d[42]),"+f"(d[43]),"+f"(d[44]),"+f"(d[45]),"+f"(d[46]),"+f"(d[47]),"+f"(d[48]),"+f"(d[49]),"+f"(d[50]),"+f"(d[51]),"+f"(d[52]),"+f"(d[53]),"+f"(d[54]),"+f"(d[55]),"+f"(d[56]),"+f"(d[57]),"+f"(d[58]),"+f"(d[59]),"+f"(d[60]),"+f"(d[61]),"+f"(d[62]),"+f"(d[63]) : "r"(alo), "r"(ahi), "r"(blo), "r"(bhi), "r"(sd));
}
__device__ __forceinline__ void wgmma_ss_n64(float (&d)[32], uint32_t alo, uint32_t ahi, uint32_t blo, uint32_t bhi, int sd) {
  asm volatile("{\n.reg .pred p;\n.reg .b64 da, db;\nsetp.ne.b32 p, %36, 0;\nmov.b64 da, {%32, %33};\nmov.b64 db, {%34, %35};\n"
    "wgmma.mma_async.sync.aligned.m64n64k16.f32.bf16.bf16 {%0,%1,%2,%3,%4,%5,%6,%7,%8,%9,%10,%11,%12,%13,%14,%15,%16,%17,%18,%19,%20,%21,%22,%23,%24,%25,%26,%27,%28,%29,%30,%31}, da, db, p, 1, 1, 0, 1;\n}"
    : "+f"(d[0]),"+f"(d[1]),"+f"(d[2]),"+f"(d[3]),"+f"(d[4]),"+f"(d[5]),"+f"(d[6]),"+f"(d[7]),"+f"(d[8]),"+f"(d[9]),"+f"(d[10]),"+f"(d[11]),"+f"(d[12]),"+f"(d[13]),"+f"(d[14]),"+f"(d[15]),"+f"(d[16]),"+f"(d[17]),"+f"(d[18]),"+f"(d[19]),"+f"(d[20]),"+f"(d[21]),"+f"(d[22]),"+f"(d[23]),"+f"(d[24]),"+f"(d[25]),"+f"(d[26]),"+f"(d[27]),"+f"(d[28]),"+f"(d[29]),"+f"(d[30]),"+f"(d[31]) : "r"(alo), "r"(ahi), "r"(blo), "r"(bhi), "r"(sd));
}
__device__ __forceinline__ void wgmma_rs_n64(float (&d)[32], uint32_t a0, uint32_t a1, uint32_t a2, uint32_t a3, uint32_t blo, uint32_t bhi, int sd) {
  asm volatile("{\n.reg .pred p;\n.reg .b64 db;\nsetp.ne.b32 p, %38, 0;\nmov.b64 db, {%36, %37};\n"
    "wgmma.mma_async.sync.aligned.m64n64k16.f32.bf16.bf16 {%0,%1,%2,%3,%4,%5,%6,%7,%8,%9,%10,%11,%12,%13,%14,%15,%16,%17,%18,%19,%20,%21,%22,%23,%24,%25,%26,%27,%28,%29,%30,%31}, {%32,%33,%34,%35}, db, p, 1, 1, 0;\n}"
    : "+f"(d[0]),"+f"(d[1]),"+f"(d[2]),"+f"(d[3]),"+f"(d[4]),"+f"(d[5]),"+f"(d[6]),"+f"(d[7]),"+f"(d[8]),"+f"(d[9]),"+f"(d[10]),"+f"(d[11]),"+f"(d[12]),"+f"(d[13]),"+f"(d[14]),"+f"(d[15]),"+f"(d[16]),"+f"(d[17]),"+f"(d[18]),"+f"(d[19]),"+f"(d[20]),"+f"(d[21]),"+f"(d[22]),"+f"(d[23]),"+f"(d[24]),"+f"(d[25]),"+f"(d[26]),"+f"(d[27]),"+f"(d[28]),"+f"(d[29]),"+f"(d[30]),"+f"(d[31]) : "r"(a0), "r"(a1), "r"(a2), "r"(a3), "r"(blo), "r"(bhi), "r"(sd));
}

__device__ __forceinline__ void bar_arrive(int id, int n) { asm volatile("bar.arrive %0, %1;" ::"r"(id), "r"(n) : "memory"); }
__device__ __forceinline__ void mbar_arrive(uint32_t bar) {
  asm volatile("mbarrier.arrive.shared::cta.b64 _, [%0];" ::"r"(bar) : "memory");
}
__device__ __forceinline__ uint32_t wslot(int r) { return (uint32_t)(8 + (r >= 4 ? r - 4 : r + 2)); }
__device__ __forceinline__ uint32_t hoff(int i) { return (uint32_t)(i < 2 ? i * 8192 : 10 * SLOT + i * 8192); }

__device__ __forceinline__ void store_pair(__nv_bfloat16* rowp, int jj, int t, uint32_t v0, uint32_t v1) {
  const bool odd = t & 1;
  uint32_t send = odd ? v0 : v1;
  uint32_t recv = __shfl_xor_sync(0xffffffffu, send, 1);
  uint2 o;
  o.x = odd ? recv : v0;
  o.y = odd ? v1 : recv;
  int col = odd ? (8 * (jj + 1) + 2 * (t - 1)) : (8 * jj + 2 * t);
  *reinterpret_cast<uint2*>(rowp + col) = o;
}

template <int U>
__device__ __forceinline__ void geglu_unit(const float (&old)[64], __nv_bfloat16* h0, int t) {
  constexpr int jj = 2 * U;
  uint32_t a0 = pack_bf16(geglu(old[4 * jj + 0], old[32 + 4 * jj + 0]), geglu(old[4 * jj + 1], old[32 + 4 * jj + 1]));
  uint32_t b0 = pack_bf16(geglu(old[4 * jj + 2], old[32 + 4 * jj + 2]), geglu(old[4 * jj + 3], old[32 + 4 * jj + 3]));
  uint32_t a1 = pack_bf16(geglu(old[4 * jj + 4], old[32 + 4 * jj + 4]), geglu(old[4 * jj + 5], old[32 + 4 * jj + 5]));
  uint32_t b1 = pack_bf16(geglu(old[4 * jj + 6], old[32 + 4 * jj + 6]), geglu(old[4 * jj + 7], old[32 + 4 * jj + 7]));
  store_pair(h0, jj, t, a0, a1);
  store_pair(h0 + (size_t)8 * F_DIM, jj, t, b0, b1);
}

__device__ __forceinline__ void g2_chunk(float (&acc)[64], uint32_t bars, int st, int par, int sd) {
  mbar_wait(bars + 8 * (B_GFULL + st), par);
  const uint32_t da = desc_lo(hoff(st), 16);
  const uint32_t db = desc_lo((1 + st) * SLOT, 8192);
  wg_fence();
#pragma unroll
  for (int k = 0; k < 4; k++) wgmma_ss_n128(acc, da + 2 * k, HI_SW128, db + 128 * k, HI_SW128, k ? 1 : sd);
  wg_commit();
}

template <int G>
__device__ __forceinline__ void conv_lda(uint32_t (&ar)[16], uint32_t abase) {
#pragma unroll
  for (int i = 0; i < 4; i++) {
    const uint32_t a = abase - 512 * G - 64 * i;
    ar[4 * i + 0] = lds32(a);
    ar[4 * i + 1] = lds32(a - 256);
    ar[4 * i + 2] = lds32(a + 16);
    ar[4 * i + 3] = lds32(a - 240);
  }
}
template <int G>
__device__ __forceinline__ void conv_issue(float (&ca)[32], float (&cb)[32], const uint32_t (&ar)[16], uint32_t dsc) {
  wg_fence();
#pragma unroll
  for (int i = 0; i < 4; i++) {
    const int sd = (G == 0 && i == 0) ? 0 : 1;
    if (G < 4) wgmma_rs_n64(ca, ar[4 * i], ar[4 * i + 1], ar[4 * i + 2], ar[4 * i + 3], dsc + 16 * G + 2 * i + 64, HI_NONE, sd);
    wgmma_rs_n64(cb, ar[4 * i], ar[4 * i + 1], ar[4 * i + 2], ar[4 * i + 3], dsc + 16 * G + 2 * i, HI_NONE, sd);
  }
  wg_commit();
}
__device__ __forceinline__ void conv_build_h(uint32_t xb, const uint4& hw0, const uint4& hw1, uint32_t hprev) {
  sts128(xb + CV_HCOPY, prmt(hw1.w, 0, 0x1032), prmt(hw1.z, 0, 0x1032), prmt(hw1.y, 0, 0x1032), prmt(hw1.x, 0, 0x1032));
  sts128(xb + CV_HCOPY + 16, prmt(hw0.w, 0, 0x1032), prmt(hw0.z, 0, 0x1032), prmt(hw0.y, 0, 0x1032), prmt(hw0.x, 0, 0x1032));
  sts128(xb, prmt(hw1.w, hw1.z, 0x7610), prmt(hw1.z, hw1.y, 0x7610), prmt(hw1.y, hw1.x, 0x7610), prmt(hw1.x, hw0.w, 0x7610));
  sts128(xb + 16, prmt(hw0.w, hw0.z, 0x7610), prmt(hw0.z, hw0.y, 0x7610), prmt(hw0.y, hw0.x, 0x7610), prmt(hw0.x, hprev, 0x5410));
}
__device__ __forceinline__ void conv_output(uint32_t sb, uint32_t ubuf, int tid, uint32_t d2, __nv_bfloat16* yrow, int en) {
  const int half = tid & 1;
#pragma unroll
  for (int i = 0; i < 2; i++) {
    const int n = (tid >> 1) + 64 * i;
    const uint4 uu = lds128(ubuf + half * CV_UHALF + (127 - n) * 16);
    const int pos = (16 * n + 8 * half) ^ (((n >> 1) & 3) << 3);
    uint4 pa = lds128(sb + CV_P + 4 * pos), pc = lds128(sb + CV_P + 4 * pos + 16);
    float f0 = __uint_as_float(pa.x), f1 = __uint_as_float(pa.y), f2 = __uint_as_float(pa.z), f3 = __uint_as_float(pa.w);
    float f4 = __uint_as_float(pc.x), f5 = __uint_as_float(pc.y), f6 = __uint_as_float(pc.z), f7 = __uint_as_float(pc.w);
    {
      uint4 pb = lds128(sb + CV_P + 8192 + 4 * pos), pd = lds128(sb + CV_P + 8192 + 4 * pos + 16);
      f0 += __uint_as_float(pb.x); f1 += __uint_as_float(pb.y); f2 += __uint_as_float(pb.z); f3 += __uint_as_float(pb.w);
      f4 += __uint_as_float(pd.x); f5 += __uint_as_float(pd.y); f6 += __uint_as_float(pd.z); f7 += __uint_as_float(pd.w);
    }
    uint4 yo;
    yo.x = badd2(pack_bf16(f0, f1), bmul2(uu.x, d2));
    yo.y = badd2(pack_bf16(f2, f3), bmul2(uu.y, d2));
    yo.z = badd2(pack_bf16(f4, f5), bmul2(uu.z, d2));
    yo.w = badd2(pack_bf16(f6, f7), bmul2(uu.w, d2));
    asm volatile("{\n.reg .pred p;\nsetp.ne.b32 p, %5, 0;\n@p st.global.v4.b32 [%0], {%1,%2,%3,%4};\n}"
                 ::"l"(yrow + 1024 * i), "r"(yo.x), "r"(yo.y), "r"(yo.z), "r"(yo.w), "r"(en) : "memory");
  }
}

__global__ void __cluster_dims__(2, 1, 1) __launch_bounds__(NTHREADS, 1)
fused_kernel(const __grid_constant__ Maps maps, const __nv_bfloat16* __restrict__ q, const __nv_bfloat16* __restrict__ kin,
             const __nv_bfloat16* __restrict__ vin, const __nv_bfloat16* __restrict__ shift_k,
             const __nv_bfloat16* __restrict__ ssm_k, const __nv_bfloat16* __restrict__ ssm_D,
             const __nv_bfloat16* __restrict__ gate_w, __nv_bfloat16* __restrict__ out) {
  extern __shared__ uint8_t smem_raw[];
  uint32_t sb;
  asm volatile("mov.u32 %0, %1;" : "=r"(sb) : "r"((s2u(smem_raw) + 1023u) & ~1023u));
  if ((sb & 0xFFFFFFu) != SB0) __trap();
  const uint32_t bars = sb + OFF_BAR;
  const int warp = __shfl_sync(0xffffffffu, (int)(threadIdx.x >> 5), 0), lane = threadIdx.x & 31;
  const int b = blockIdx.x;
  const int rank = b & 1, pair = b >> 1;
  const int f = pair & 7, m1 = 2 * (pair >> 3) + rank;
  const int m2 = pair >> 2, r2 = 2 * m2 + rank, cb = pair & 3;

  if (lane == 0) {
    if (warp < 9) prefetch_map(reinterpret_cast<const CUtensorMap*>(&maps) + warp);
#pragma unroll
    for (int k = 0; k < 4; k++) {
      const int i = 4 * warp + k;
      int cnt = 1;
      if (i >= B_XEMPTY && i < B_WFULL) cnt = 5;
      else if (i >= B_WEMPTY && i < B_GFULL) cnt = 4;
      else if (i >= B_GEMPTY && i < B_QFULL) cnt = 2;
      mbar_init(bars + 8 * i, cnt);
    }
    asm volatile("fence.mbarrier_init.release.cluster;" ::: "memory");
    fence_proxy_smem();
  }
  if (threadIdx.x == 0) PROF(56);
  __syncthreads();
  asm volatile("barrier.cluster.arrive.relaxed.aligned;" ::: "memory");
  if (warp >= 8 && warp < 10 && lane == 0) {
#pragma unroll 1
    for (int c = warp - 8; c < 4; c += 2) {
      mbar_expect(bars + 8 * (B_XFULL + c), SLOT);
      tma2d(sb + c * SLOT, &maps.x, 64 * c, 128 * m1, bars + 8 * (B_XFULL + c));
    }
  }
  __syncwarp();
  asm volatile("barrier.cluster.wait.aligned;" ::: "memory");
  if (threadIdx.x == 0) PROF(58);

  if (warp < 8) {
    asm volatile("setmaxnreg.inc.sync.aligned.u32 168;");
    const int wg = warp >> 2, wl = warp & 3, g = lane >> 2, t = lane & 3;
    const bool elect = (threadIdx.x & 127) == 0;
    const float nz = __uint_as_float(0x80000000u | (uint32_t)(blockIdx.y));
    const uint32_t dxa = desc_lo(wg * 8192, 16);
    __nv_bfloat16* hrow = g_H + (size_t)(128 * m1 + 64 * wg + 16 * wl + g) * F_DIM;
    __nv_bfloat16* hlast;
    float old[64];
    if (elect) PROF(0 + 16 * wg);
    {
      float a0[32];
#pragma unroll
      for (int s = 0; s < 4; s++) {
        mbar_wait(bars + 8 * (B_XFULL + 2 * s), 0);
        mbar_wait(bars + 8 * (B_XFULL + 2 * s + 1), 0);
        mbar_wait(bars + 8 * (B_WFULL + s), 0);
        if (s == 0 && elect) PROF(1 + 16 * wg);
        const uint32_t db = desc_lo((10 + s) * SLOT, 8192);
        wg_fence();
#pragma unroll
        for (int k = 0; k < 4; k++) wgmma_ss_n64(a0, dxa + (2 * s) * 1024 + 2 * k, HI_SW128, db + 64 * k, HI_SW64, (s | k) != 0);
#pragma unroll
        for (int k = 0; k < 4; k++) wgmma_ss_n64(a0, dxa + (2 * s + 1) * 1024 + 2 * k, HI_SW128, db + 64 * (4 + k), HI_SW64, 1);
        wg_commit();
        if (s > 0) {
          wg_wait<1>();
          if (elect) mbar_arrive_both(bars + 8 * (B_WEMPTY + s - 1));
        }
      }
      wg_wait<0>();
      if (elect) mbar_arrive_both(bars + 8 * (B_WEMPTY + 3));
#pragma unroll
      for (int i = 0; i < 16; i++) { old[i] = a0[i] + nz; old[32 + i] = a0[16 + i] + nz; old[16 + i] = 0.f; old[48 + i] = 0.f; }
      if (elect) PROF(2 + 16 * wg);
    }
    {
      int r = 4, par = 0;
      __nv_bfloat16* hout = hrow + 32 * f;
#pragma unroll 1
      for (int j = 1; j < 4; j++) {
        float acc[64];
        int prev = 0;
#pragma unroll
        for (int s = 0; s < 8; s++) {
          mbar_wait(bars + 8 * (B_WFULL + r), par);
          const uint32_t db = desc_lo(wslot(r) * SLOT, 4096);
          wg_fence();
#pragma unroll
          for (int k = 0; k < 4; k++) wgmma_ss_n128(acc, dxa + s * 1024 + 2 * k, HI_SW128, db + 64 * k, HI_SW64, (s | k) != 0);
          wg_commit();
          if (s == 1) geglu_unit<0>(old, hout, t);
          if (s == 3) geglu_unit<1>(old, hout, t);
          if (s == 5 && j > 1) geglu_unit<2>(old, hout, t);
          if (s == 7 && j > 1) geglu_unit<3>(old, hout, t);
          if (s > 0) {
            wg_wait<1>();
            if (elect) {
              mbar_arrive_both(bars + 8 * ((j == 3 && s >= 3) ? (B_WLAST + s - 3) : (B_WEMPTY + prev)));
              if (j == 3) mbar_arrive_both(bars + 8 * (B_XEMPTY + s - 1));
            }
          }
          prev = r;
          if (++r == 6) { r = 0; par ^= 1; }
        }
        fence_proxy_async();
        bar_arrive(4 + j - 1, 288);
        wg_wait<0>();
        if (elect) {
          mbar_arrive_both(bars + 8 * (j == 3 ? (B_WLAST + 5) : (B_WEMPTY + prev)));
          if (j == 3) mbar_arrive_both(bars + 8 * (B_XEMPTY + 7));
        }
#pragma unroll
        for (int i = 0; i < 64; i++) old[i] = acc[i] + nz;
        hout = hrow + 256 + 512 * (j - 1) + 64 * f;
        if (elect) PROF(2 + j + 16 * wg);
      }
      hlast = hout;
    }
    float acc[64];
    {
      geglu_unit<0>(old, hlast, t);
      g2_chunk(acc, bars, wg, 0, 0);
      geglu_unit<1>(old, hlast, t);
      geglu_unit<2>(old, hlast, t);
      g2_chunk(acc, bars, wg + 2, 0, 1);
      geglu_unit<3>(old, hlast, t);
      fence_proxy_async();
      bar_arrive(7, 288);
      if (elect) PROF(7 + 16 * wg);
      wg_wait<1>();
      if (elect) mbar_arrive_both(bars + 8 * (B_GEMPTY + wg));
      int st = wg + 4, par = 0, prev = wg + 2;
#pragma unroll 1
      for (int kk = 2; kk < 14; kk++) {
        g2_chunk(acc, bars, st, par, 1);
        if (elect) PROF(64 + 2 * kk + wg);
        wg_wait<1>();
        if (elect) mbar_arrive_both(bars + 8 * (B_GEMPTY + prev));
        prev = st;
        st += 2;
        if (st >= GRING) { st -= GRING; par ^= 1; }
      }
      wg_wait<0>();
    }
    if (elect) PROF(11 + 16 * wg);
    {
      const uint32_t tl = (threadIdx.x & 127) * 16;
      bar_sync(9, 256);
#pragma unroll
      for (int i = 0; i < 8; i++) {
        const int e = 4 * i;
        if (wg == 0) sts128(sb + 4 * SLOT + i * 2048 + tl, __float_as_uint(acc[32 + e]), __float_as_uint(acc[33 + e]), __float_as_uint(acc[34 + e]), __float_as_uint(acc[35 + e]));
        else sts128(sb + 5 * SLOT + i * 2048 + tl, __float_as_uint(acc[e]), __float_as_uint(acc[1 + e]), __float_as_uint(acc[2 + e]), __float_as_uint(acc[3 + e]));
      }
      bar_sync(9, 256);
#pragma unroll
      for (int i = 0; i < 8; i++) {
        const uint4 v = lds128(sb + (5 - wg) * SLOT + i * 2048 + tl);
        const int e = 4 * i;
        old[e + 0] = (wg ? acc[32 + e] : acc[e]) + __uint_as_float(v.x);
        old[e + 1] = (wg ? acc[33 + e] : acc[1 + e]) + __uint_as_float(v.y);
        old[e + 2] = (wg ? acc[34 + e] : acc[2 + e]) + __uint_as_float(v.z);
        old[e + 3] = (wg ? acc[35 + e] : acc[3 + e]) + __uint_as_float(v.w);
      }
    }
    mbar_wait(bars + 8 * B_QFULL, 0);
    if (elect) PROF(12 + 16 * wg);
    {
      const int r0 = 16 * wl + g;
      const float g0 = __uint_as_float(lds32(sb + OFF_GATE + 4 * r0));
      const float g1 = __uint_as_float(lds32(sb + OFF_GATE + 4 * (r0 + 8)));
      const uint32_t g0p = pack_bf16(g0, g0), g1p = pack_bf16(g1, g1);
      const uint32_t o0p = pack_bf16(1.0f - g0, 1.0f - g0), o1p = pack_bf16(1.0f - g1, 1.0f - g1);
      const int mi = lane >> 3, l7 = lane & 7;
      const int qrow = 16 * wl + l7 + 8 * (mi & 1);
      const uint32_t qaddr = sb + 1 * SLOT + wg * 8192 + qrow * 128;
      const int ych = 8 * (mi >> 1) + l7;
      const uint32_t yaddr = sb + 2 * SLOT + wg * 8192 + ych * 128 + (((2 * wl + (mi & 1)) ^ l7) << 4);
      __nv_bfloat16* o0 = out + (size_t)(64 * r2 + r0) * D_DIM + 128 * cb + 64 * wg;
      __nv_bfloat16* o1 = o0 + 8 * D_DIM;
#pragma unroll
      for (int jj = 0; jj < 8; jj += 2) {
        uint32_t q0, q1, q2, q3, y0, y1, y2, y3;
        ldsm4(qaddr + (((jj + (mi >> 1)) ^ l7) << 4), q0, q1, q2, q3);
        ldsm4t(yaddr + jj * 1024, y0, y1, y2, y3);
        uint32_t r00 = badd2(bmul2(g0p, bmul2(q0, y0)), bmul2(o0p, pack_bf16(old[4 * jj + 0], old[4 * jj + 1])));
        uint32_t r10 = badd2(bmul2(g1p, bmul2(q1, y1)), bmul2(o1p, pack_bf16(old[4 * jj + 2], old[4 * jj + 3])));
        uint32_t r01 = badd2(bmul2(g0p, bmul2(q2, y2)), bmul2(o0p, pack_bf16(old[4 * jj + 4], old[4 * jj + 5])));
        uint32_t r11 = badd2(bmul2(g1p, bmul2(q3, y3)), bmul2(o1p, pack_bf16(old[4 * jj + 6], old[4 * jj + 7])));
        store_pair(o0, jj, t, r00, r01);
        store_pair(o1, jj, t, r10, r11);
      }
    }
    if (elect) PROF(13 + 16 * wg);
    asm volatile("barrier.cluster.arrive.relaxed.aligned;\nbarrier.cluster.wait.aligned; // gemm" ::: "memory");
    if (threadIdx.x == 0) { PROF(14); PROFG(62); }
    if (threadIdx.x == 0) atomicAdd(&g_cnt[C_DONE * 32], 1u);
  } else if (warp < 12) {
    asm volatile("setmaxnreg.inc.sync.aligned.u32 152;");
    const int tid = threadIdx.x - 256, wl = warp - 8, g = lane >> 2, t = lane & 3;
    {
      const uint4 w0 = ldg128(reinterpret_cast<const uint4*>(gate_w) + lane);
      const uint4 w1 = ldg128(reinterpret_cast<const uint4*>(gate_w) + 32 + lane);
#pragma unroll 1
      for (int c = 0; c < 8; c++) mbar_wait(bars + 8 * (B_XFULL + c), 0);
      uint4 x0[4], x1[4];
#pragma unroll
      for (int i = 0; i < 4; i++) {
        const int row = 16 * f + 4 * wl + i;
        const uint32_t a = sb + (lane >> 3) * SLOT + row * 128 + (((lane & 7) ^ (row & 7)) << 4);
        x0[i] = lds128(a);
        x1[i] = lds128(a + 4 * SLOT);
      }
      float sm[4];
#pragma unroll
      for (int i = 0; i < 4; i++) {
        const uint32_t p[8] = {bmul2(x0[i].x, w0.x), bmul2(x0[i].y, w0.y), bmul2(x0[i].z, w0.z), bmul2(x0[i].w, w0.w),
                               bmul2(x1[i].x, w1.x), bmul2(x1[i].y, w1.y), bmul2(x1[i].z, w1.z), bmul2(x1[i].w, w1.w)};
        sm[i] = ((bf_lo(p[0]) + bf_hi(p[0])) + (bf_lo(p[1]) + bf_hi(p[1]))) + ((bf_lo(p[2]) + bf_hi(p[2])) + (bf_lo(p[3]) + bf_hi(p[3]))) +
                ((bf_lo(p[4]) + bf_hi(p[4])) + (bf_lo(p[5]) + bf_hi(p[5]))) + ((bf_lo(p[6]) + bf_hi(p[6])) + (bf_lo(p[7]) + bf_hi(p[7])));
      }
      bar_sync(3, 128);
      if (tid < 8) mbar_arrive(bars + 8 * (B_XEMPTY + tid));
#pragma unroll
      for (int o = 16; o > 0; o >>= 1)
#pragma unroll
        for (int i = 0; i < 4; i++) sm[i] += __shfl_xor_sync(0xffffffffu, sm[i], o);
      const float z = bf_round(lane == 0 ? sm[0] : lane == 1 ? sm[1] : lane == 2 ? sm[2] : sm[3]);
      if (lane < 4) g_gate[128 * m1 + 16 * f + 4 * wl + lane] = bf_round(1.0f / (1.0f + __expf(-z)));
    }
    if (tid == 0) PROF(32);
    {
      const int blk = tid & 1;
      const int s0 = 32 * (b >> 1) + 16 * blk;
      uint32_t kr[2][19], vr[2][16];
      uint4 sk[2];
#pragma unroll
      for (int i = 0; i < 2; i++) {
        const int c0 = 256 * (b & 1) + 2 * ((tid >> 1) + 64 * i);
        const __nv_bfloat16* kp = kin + (size_t)s0 * D_DIM + c0;
        const __nv_bfloat16* vp = vin + (size_t)s0 * D_DIM + c0;
        sk[i] = ldg128(shift_k + 4 * c0);
#pragma unroll
        for (int r = 0; r < 19; r++) kr[i][r] = (r >= 3 || s0 > 0) ? ldg32(kp + (r - 3) * D_DIM) : 0u;
#pragma unroll
        for (int r = 0; r < 16; r++) vr[i][r] = ldg32(vp + r * D_DIM);
      }
#pragma unroll
      for (int i = 0; i < 2; i++) {
        const int c0 = 256 * (b & 1) + 2 * ((tid >> 1) + 64 * i);
        const uint32_t sk0 = prmt(sk[i].x, sk[i].z, 0x5410), sk1 = prmt(sk[i].x, sk[i].z, 0x7632);
        const uint32_t sk2 = prmt(sk[i].y, sk[i].w, 0x5410), sk3 = prmt(sk[i].y, sk[i].w, 0x7632);
#pragma unroll
        for (int r = 0; r < 16; r++) {
          uint32_t a = bmul2(kr[i][r], sk3);
          a = badd2(a, bmul2(kr[i][r + 1], sk2));
          a = badd2(a, bmul2(kr[i][r + 2], sk1));
          a = badd2(a, bmul2(kr[i][r + 3], sk0));
          vr[i][r] = bmul2(a, vr[i][r]);
        }
        uint4* up = g_u + c0 * 256 + (127 - (s0 >> 4));
#pragma unroll
        for (int ch = 0; ch < 2; ch++) {
          const uint32_t sel = ch ? 0x7632 : 0x5410;
#pragma unroll
          for (int half = 0; half < 2; half++) {
            const int e = 8 * half;
            uint4 o;
            o.x = prmt(vr[i][e + 0], vr[i][e + 1], sel);
            o.y = prmt(vr[i][e + 2], vr[i][e + 3], sel);
            o.z = prmt(vr[i][e + 4], vr[i][e + 5], sel);
            o.w = prmt(vr[i][e + 6], vr[i][e + 7], sel);
            up[ch * 256 + half * 128] = o;
          }
        }
      }
      fence_proxy_async();
      bar_sync(3, 128);
      if (tid == 0) PROF(33);
      if (tid == 0) flag_signal(C_PRE);
      if (tid == 0) PROF(34);
    }
    const int ch0 = 4 * b;
    const uint2 dall = *reinterpret_cast<const uint2*>(ssm_D + ch0);
    mbar_wait(bars + 8 * (B_WLAST + 0), 0);
    mbar_wait(bars + 8 * (B_WLAST + 1), 0);
    mbar_wait(bars + 8 * (B_WLAST + 2), 0);
    if (tid == 0) PROF(35);
    {
      const int arr = tid >> 5, r = tid & 31;
      sts128(sb + CV_U + arr * CV_UHALF + 2048 + r * 16, 0, 0, 0, 0);
      if (r < 24) sts128(sb + CV_U + arr * CV_UHALF + 2048 + 512 + r * 16, 0, 0, 0, 0);
      else if (r == 24) sts128(sb + CV_H + (arr >> 1) * CV_HCOPY + 4096 + (arr & 1) * 16, 0, 0, 0, 0);
      else if (r == 25) sts128(sb + CV_P + 8192 + arr * 16, 0, 0, 0, 0);
      else if (r == 26) sts128(sb + CV_HRAW, 0, 0, 0, 0);
    }
    fence_proxy_smem();
    const int o1 = 8 * (wl & 1) + g + 16 * (wl >> 1);
    const uint32_t abase = sb + CV_H + (g & 1) * CV_HCOPY + 2 * ((2046 + (g & 1)) - o1 + 2 * t);

    uint32_t pst0, pst1;
    const bool pst_ok = !(t == 0 && wl >= 2);
    {
      const int r0 = 8 * (wl & 1) + g;
      const int s0 = 16 * (127 - 2 * t + (wl >> 1)) + r0, s1 = s0 - 16;
      pst0 = sb + CV_P + (wl >> 1) * 8192 + 4 * (s0 ^ (((s0 >> 5) & 3) << 3));
      pst1 = sb + CV_P + (wl >> 1) * 8192 + 4 * (s1 ^ (((s1 >> 5) & 3) << 3));
    }
    bar_sync(3, 128);
#pragma unroll 1
    for (int c = DBG(1) ? 4 : 0; c < 4; c++) {
      const int buf = c & 1;
      mbar_wait(bars + 8 * (B_CFULL + c), 0);
      {
        const uint32_t hr = sb + CV_HRAW + 16 + 32 * tid;
        const uint4 hw0 = lds128(hr), hw1 = lds128(hr + 16);
        conv_build_h(sb + CV_H + 2 * (2032 - 16 * tid), hw0, hw1, lds32(hr - 4) >> 16);
      }
      bar_sync(3, 128);
      if (tid == 0) PROF(37 + 3 * c);
      const uint32_t dsc = desc_lo(CV_U + buf * CV_UCH, CV_UHALF);
      float ca[32], cb[32];
      uint32_t ra[16], rb[16], rc[16];
      conv_lda<0>(ra, abase);
      conv_issue<0>(ca, cb, ra, dsc);
      PROFX(144 + 16 * (c >> 1) + 0, tid == 0 && (c & 1));
      conv_lda<1>(rb, abase);
      conv_issue<1>(ca, cb, rb, dsc);
      PROFX(144 + 16 * (c >> 1) + 1, tid == 0 && (c & 1));
      {
        const uint32_t d2 = prmt(((c - 1) & 2) ? dall.y : dall.x, 0, ((c - 1) & 1) ? 0x3232 : 0x1010);
        conv_output(sb, sb + CV_U + (buf ^ 1) * CV_UCH, tid, d2, g_yT + ((ch0 + c - 1) * S_LEN + 8 * tid), c);
      }
      PROFX(144 + 16 * (c >> 1) + 2, tid == 0 && (c & 1));
      bar_sync(c < 3 ? 8 : 3, c < 3 ? 160 : 128);
      PROFX(144 + 16 * (c >> 1) + 3, tid == 0 && (c & 1));
      wg_wait<1>();
      conv_lda<2>(ra, abase);
      conv_issue<2>(ca, cb, ra, dsc);
      PROFX(144 + 16 * (c >> 1) + 4, tid == 0 && (c & 1));
      wg_wait<1>();
      conv_lda<3>(rb, abase);
      conv_issue<3>(ca, cb, rb, dsc);
      PROFX(144 + 16 * (c >> 1) + 5, tid == 0 && (c & 1));
      wg_wait<1>();
      conv_lda<4>(ra, abase);
      conv_issue<4>(ca, cb, ra, dsc);
      PROFX(144 + 16 * (c >> 1) + 6, tid == 0 && (c & 1));
      wg_wait<1>();
#pragma unroll
      for (int jj = 8; jj < 16; jj++)
#pragma unroll
        for (int e = 0; e < 2; e++) {
          float v = ca[4 * (jj - 8) + e];
          if (jj < 15) v += ca[4 * (jj + 1 - 8) + 2 + e];
          sts32((e ? pst1 : pst0) - 512 * jj, __float_as_uint(v));
        }
      const float e0 = ca[2], e1 = ca[3];
      PROFX(144 + 16 * (c >> 1) + 7, tid == 0 && (c & 1));
      conv_lda<5>(rb, abase);
      conv_lda<6>(rc, abase);
      conv_issue<5>(ca, cb, rb, dsc);
      conv_issue<6>(ca, cb, rc, dsc);
      PROFX(144 + 16 * (c >> 1) + 8, tid == 0 && (c & 1));
      wg_wait<2>();
      conv_lda<7>(ra, abase);
      conv_issue<7>(ca, cb, ra, dsc);
      PROFX(144 + 16 * (c >> 1) + 9, tid == 0 && (c & 1));
      wg_wait<0>();
      if (tid == 0) PROF(38 + 3 * c);
#pragma unroll
      for (int jj = 0; jj < 8; jj++)
#pragma unroll
        for (int e = 0; e < 2; e++) {
          float v = cb[4 * jj + e] + (jj < 7 ? cb[4 * (jj + 1) + 2 + e] : (e ? e1 : e0));
          if (jj > 0 || e > 0 || pst_ok) sts32((e ? pst1 : pst0) - 512 * jj, __float_as_uint(v));
        }
      bar_sync(3, 128);
      if (tid == 0) PROF(39 + 3 * c);
    }
    conv_output(sb, sb + CV_U + CV_UCH, tid, prmt(dall.y, 0, 0x3232), g_yT + ((ch0 + 3) * S_LEN + 8 * tid), 1);
    fence_proxy_async();
    bar_sync(3, 128);
    if (tid == 0) flag_signal(C_CONV + (b >> 5));
    if (tid == 0) PROF(49);
    asm volatile("barrier.cluster.arrive.relaxed.aligned;\nbarrier.cluster.wait.aligned; // conv" ::: "memory");
  } else {
    asm volatile("setmaxnreg.dec.sync.aligned.u32 24;");
    if (lane == 0) {
      const int st = warp - 12;
      mbar_expect(bars + 8 * (B_WFULL + st), SLOT);
      tma3d_mc(sb + rank * 8192 + (10 + st) * SLOT, rank ? &maps.wu0 : &maps.wg0, 0, 128 * st, f, bars + 8 * (B_WFULL + st));
    }
    if (warp == 12) {
      if (lane == 0) {
        const CUtensorMap* m1p = rank ? &maps.wu1 : &maps.wg1;
        const uint32_t doff = sb + rank * 8192;
        int r = 4, par = 1, grp = 8 + 2 * f;
#pragma unroll 1
        for (int st = 4; st < 28; st++) {
          const int s = (st - 4) & 7;
          mbar_wait(bars + 8 * (B_WEMPTY + r), par);
          mbar_expect(bars + 8 * (B_WFULL + r), SLOT);
          tma3d_mc(doff + wslot(r) * SLOT, m1p, 0, 64 * s, grp, bars + 8 * (B_WFULL + r));
          if (s == 7) grp += 16;
          if (++r == 6) { r = 0; par ^= 1; }
        }
        flag_wait(C_PRE, read_epoch() * NCTA);
        fence_proxy_async();
        mbar_wait(bars + 8 * (B_WLAST + 0), 0);
        mbar_wait(bars + 8 * (B_WLAST + 1), 0);
      }
#pragma unroll 1
      for (int c = 0; c < 4; c++) {
        if (c >= 1) bar_sync(8, 160);
        if (lane == 0) {
          const uint32_t dst = sb + CV_U + (c & 1) * CV_UCH, fb = bars + 8 * (B_CFULL + c);
          mbar_expect(fb, 8192);
          bulk_g2s(sb + CV_HRAW + 16, ssm_k + (size_t)(4 * b + c) * S_LEN, 4096, fb);
          bulk_g2s(dst, g_u + (4 * b + c) * 256, 2048, fb);
          bulk_g2s(dst + CV_UHALF, g_u + (4 * b + c) * 256 + 128, 2048, fb);
        }
        __syncwarp();
      }
    } else if (warp == 13) {
      if (lane == 0) {
        const unsigned target = read_epoch() * 8;
        int st = 0, par = 1;
#pragma unroll 1
        for (int c = 0; c < 28; c++) {
          if (((c & 7) == 4) | (c == 0)) {
            flag_wait(C_FH + 4 * m2 + ((c + 4) >> 3), target);
            fence_proxy_async();
          }
          if (c < GRING) mbar_wait(bars + 8 * (c < 2 ? B_XEMPTY : B_WLAST + 2 + (c >> 1)), 0);
          else mbar_wait(bars + 8 * (B_GEMPTY + st), par);
          tma2d(sb + hoff(st), &maps.h, 64 * c, 64 * r2, bars + 8 * (B_GFULL + st));
          PROF(96 + c);
          if (++st == GRING) { st = 0; par ^= 1; }
        }
      }
    } else if (warp == 14) {
      if (lane == 0) {
#pragma unroll 1
        for (int c = 4; c < 8; c++) {
          mbar_wait(bars + 8 * (B_XFULL + c - 4), 0);
          mbar_expect(bars + 8 * (B_XFULL + c), SLOT);
          tma2d(sb + c * SLOT, &maps.x, 64 * c, 128 * m1, bars + 8 * (B_XFULL + c));
        }
        const unsigned ep = read_epoch();
        const uint32_t doff = sb + SLOT + rank * 8192;
        int st = 0, par = 1;
#pragma unroll 1
        for (int c = 0; c < 28; c++) {
          if (c < GRING) mbar_wait(bars + 8 * (B_XEMPTY + 1 + c), 0);
          else mbar_wait(bars + 8 * (B_GEMPTY + st), par);
          mbar_expect(bars + 8 * (B_GFULL + st), SLOT + 8192);
          tma2d_mc(doff + st * SLOT, &maps.wd, 128 * cb + 64 * rank, 64 * c, bars + 8 * (B_GFULL + st));
          if (++st == GRING) { st = 0; par ^= 1; }
        }
        const uint32_t fb = bars + 8 * B_QFULL;
        mbar_wait(bars + 8 * (B_GEMPTY + 0), 1);
        mbar_expect(fb, 2 * SLOT + 256);
        tma2d(sb + SLOT, &maps.xq, 128 * cb, 64 * r2, fb);
        tma2d(sb + SLOT + 8192, &maps.xq, 128 * cb + 64, 64 * r2, fb);
        PROF(54);
        flag_wait(C_PRE, ep * NCTA);
        flag_wait(C_CONV + cb, ep * 32);
        fence_proxy_async();
        PROF(55);
        mbar_wait(bars + 8 * (B_GEMPTY + 1), 1);
        tma2d(sb + 2 * SLOT, &maps.y, 64 * r2, 128 * cb, fb);
        bulk_g2s(sb + OFF_GATE, g_gate + 64 * r2, 256, fb);
      }
    } else {
#pragma unroll 1
      for (int j = 0; j < 4; j++) {
        bar_sync(4 + j, 288);
        if (lane == 0) flag_signal(C_FH + 4 * m1 + j);
        if (lane == 0) PROF(50 + j);
      }
    }
    __syncwarp();
    asm volatile("barrier.cluster.arrive.relaxed.aligned;\nbarrier.cluster.wait.aligned; // prod" ::: "memory");
  }
}

typedef CUresult (*EncFn)(CUtensorMap*, CUtensorMapDataType, cuuint32_t, void*, const cuuint64_t*, const cuuint64_t*,
                          const cuuint32_t*, const cuuint32_t*, CUtensorMapInterleave, CUtensorMapSwizzle,
                          CUtensorMapL2promotion, CUtensorMapFloatOOBfill);

void make2d(EncFn enc, CUtensorMap* m, const void* p, int cols, int rows, int bc, int br) {
  cuuint64_t gd[2] = {(cuuint64_t)cols, (cuuint64_t)rows};
  cuuint64_t gs[1] = {(cuuint64_t)cols * 2};
  cuuint32_t bx[2] = {(cuuint32_t)bc, (cuuint32_t)br};
  cuuint32_t es[2] = {1, 1};
  enc(m, CU_TENSOR_MAP_DATA_TYPE_BFLOAT16, 2, const_cast<void*>(p), gd, gs, bx, es, CU_TENSOR_MAP_INTERLEAVE_NONE,
      CU_TENSOR_MAP_SWIZZLE_128B, CU_TENSOR_MAP_L2_PROMOTION_L2_128B, CU_TENSOR_MAP_FLOAT_OOB_FILL_NONE);
}
void makeW(EncFn enc, CUtensorMap* m, const void* p, int bk, int ngroups) {
  cuuint64_t gd[3] = {32, (cuuint64_t)D_DIM, (cuuint64_t)(F_DIM / 32)};
  cuuint64_t gs[2] = {(cuuint64_t)F_DIM * 2, 64};
  cuuint32_t bx[3] = {32, (cuuint32_t)bk, (cuuint32_t)ngroups};
  cuuint32_t es[3] = {1, 1, 1};
  enc(m, CU_TENSOR_MAP_DATA_TYPE_BFLOAT16, 3, const_cast<void*>(p), gd, gs, bx, es, CU_TENSOR_MAP_INTERLEAVE_NONE,
      CU_TENSOR_MAP_SWIZZLE_64B, CU_TENSOR_MAP_L2_PROMOTION_L2_128B, CU_TENSOR_MAP_FLOAT_OOB_FILL_NONE);
}

}

extern "C" void kernel_launch(void* const* d_in, const int* in_sizes, int n_in, void* d_out, int out_size) {
  (void)in_sizes; (void)n_in; (void)out_size;
  const __nv_bfloat16* q = (const __nv_bfloat16*)d_in[0];
  const __nv_bfloat16* k = (const __nv_bfloat16*)d_in[1];
  const __nv_bfloat16* v = (const __nv_bfloat16*)d_in[2];
  const __nv_bfloat16* shift_k = (const __nv_bfloat16*)d_in[3];
  const __nv_bfloat16* ssm_k = (const __nv_bfloat16*)d_in[4];
  const __nv_bfloat16* ssm_D = (const __nv_bfloat16*)d_in[5];
  const __nv_bfloat16* w_gate = (const __nv_bfloat16*)d_in[7];
  const __nv_bfloat16* w_up = (const __nv_bfloat16*)d_in[8];
  const __nv_bfloat16* w_down = (const __nv_bfloat16*)d_in[9];
  const __nv_bfloat16* gate_w = (const __nv_bfloat16*)d_in[10];

  static EncFn enc = nullptr;
  static void* pH = nullptr;
  static void* pY = nullptr;
  if (!enc) {
    cudaDriverEntryPointQueryResult qr;
    cudaGetDriverEntryPoint("cuTensorMapEncodeTiled", (void**)&enc, cudaEnableDefault, &qr);
    cudaGetSymbolAddress(&pH, g_H);
    cudaGetSymbolAddress(&pY, g_yT);
    cudaFuncSetAttribute(fused_kernel, cudaFuncAttributeMaxDynamicSharedMemorySize, SMEM_BYTES);
  }
  Maps maps;
  make2d(enc, &maps.x, q, D_DIM, S_LEN, 64, 128);
  makeW(enc, &maps.wg0, w_gate, 128, 1);
  makeW(enc, &maps.wu0, w_up, 128, 1);
  makeW(enc, &maps.wg1, w_gate, 64, 2);
  makeW(enc, &maps.wu1, w_up, 64, 2);
  make2d(enc, &maps.h, pH, F_DIM, S_LEN, 64, 64);
  make2d(enc, &maps.wd, w_down, D_DIM, F_DIM, 64, 64);
  make2d(enc, &maps.y, pY, S_LEN, D_DIM, 64, 128);
  make2d(enc, &maps.xq, q, D_DIM, S_LEN, 64, 64);
  fused_kernel<<<NCTA, NTHREADS, SMEM_BYTES>>>(maps, q, k, v, shift_k, ssm_k, ssm_D, gate_w, (__nv_bfloat16*)d_out);
}
```

```cpp
#include <cuda_runtime.h>
#include <cuda_bf16.h>
#include <cuda.h>
#include <stdint.h>

namespace {

constexpr int S_LEN = 2048, D_DIM = 512, F_DIM = 1792;
constexpr int NCTA = 128;
constexpr int NTHREADS = 512;
constexpr uint32_t SLOT = 16384;
constexpr uint32_t OFF_BAR = 14 * SLOT;
constexpr int B_XFULL = 0, B_XEMPTY = 8, B_WFULL = 16, B_WEMPTY = 22, B_WLAST = 28, B_GFULL = 34, B_GEMPTY = 42,
              B_QFULL = 50, B_CFULL = 51, B_HRDY = 55, B_YFULL = 58, B_CDONE = 59, B_YSLOT = 63;
constexpr uint32_t OFF_GATE = OFF_BAR + 512;
constexpr uint32_t SMEM_USED = OFF_GATE + 512;
constexpr uint32_t SMEM_BYTES = SMEM_USED + 1024;
constexpr uint32_t CV_BASE = 12 * SLOT;
constexpr uint32_t CV_U = CV_BASE;
constexpr uint32_t CV_UCH = 5888, CV_UHALF = 2944;
constexpr uint32_t CV_H = CV_BASE + 11776;
constexpr uint32_t CV_HCOPY = 4160;
constexpr uint32_t CV_HRAW = CV_BASE + 20096;
constexpr uint32_t CV_Y = CV_BASE + 24320;
constexpr int GRING = 8;
constexpr int YIELD1 = 2, YIELD2 = 4;
constexpr uint32_t SPIN_LIMIT = 1u << 22;

constexpr int C_DONE = 0, C_PRE = 1, C_CONV = 2, C_FH = 10, C_PREU = 74, NCNT = 82;

__device__ __nv_bfloat16 g_H[(size_t)S_LEN * F_DIM];
__device__ uint4 g_u[D_DIM * 256];
__device__ __nv_bfloat16 g_yT[(size_t)D_DIM * S_LEN];
__device__ float g_gate[S_LEN];
__device__ unsigned g_cnt[NCNT * 32];

#define DBG(bit) 0
#define PROF(i) do {} while (0)
#define PROFG(i) do {} while (0)
#define PROFX(i, en) do {} while (0)

struct Maps {
  CUtensorMap x, wg0, wu0, wg1, wu1, h, wd, y, xq;
};

__device__ __forceinline__ uint32_t s2u(const void* p) { return (uint32_t)__cvta_generic_to_shared(p); }
__device__ __forceinline__ void mbar_init(uint32_t b, int c) {
  asm volatile("mbarrier.init.shared::cta.b64 [%0], %1;" ::"r"(b), "r"(c) : "memory");
}
__device__ __forceinline__ void mbar_expect(uint32_t b, uint32_t bytes) {
  asm volatile("mbarrier.arrive.expect_tx.shared::cta.b64 _, [%0], %1;" ::"r"(b), "r"(bytes) : "memory");
}
__device__ __forceinline__ void mbar_wait(uint32_t bar, uint32_t parity) {
  asm volatile(
      "{\n.reg .pred p;\n.reg .u32 c;\nmov.u32 c, 0;\n"
      "LW:\nmbarrier.try_wait.parity.shared::cta.b64 p, [%0], %1;\n@p bra LD;\n"
      "add.u32 c, c, 1;\nsetp.lt.u32 p, c, 4194304;\n@p bra LW;\ntrap;\nLD:\n}" ::"r"(bar), "r"(parity) : "memory");
}
__device__ __forceinline__ void mbar_arrive_both(uint32_t bar) {
  asm volatile(
      "{\n.reg .b32 r0, r1;\n"
      "mapa.shared::cluster.u32 r0, %0, 0;\n"
      "mapa.shared::cluster.u32 r1, %0, 1;\n"
      "mbarrier.arrive.shared::cluster.b64 _, [r0];\n"
      "mbarrier.arrive.shared::cluster.b64 _, [r1];\n}" ::"r"(bar) : "memory");
}
__device__ __forceinline__ void tma2d(uint32_t dst, const CUtensorMap* m, int c0, int c1, uint32_t bar) {
  asm volatile("cp.async.bulk.tensor.2d.shared::cluster.global.mbarrier::complete_tx::bytes [%0], [%1, {%3, %4}], [%2];"
               ::"r"(dst), "l"(m), "r"(bar), "r"(c0), "r"(c1) : "memory");
}
__device__ __forceinline__ void tma2d_mc(uint32_t dst, const CUtensorMap* m, int c0, int c1, uint32_t bar) {
  asm volatile("cp.async.bulk.tensor.2d.shared::cluster.global.mbarrier::complete_tx::bytes.multicast::cluster [%0], [%1, {%3, %4}], [%2], %5;"
               ::"r"(dst), "l"(m), "r"(bar), "r"(c0), "r"(c1), "h"((uint16_t)3) : "memory");
}
__device__ __forceinline__ void tma3d_mc(uint32_t dst, const CUtensorMap* m, int c0, int c1, int c2, uint32_t bar) {
  asm volatile("cp.async.bulk.tensor.3d.shared::cluster.global.mbarrier::complete_tx::bytes.multicast::cluster [%0], [%1, {%3, %4, %5}], [%2], %6;"
               ::"r"(dst), "l"(m), "r"(bar), "r"(c0), "r"(c1), "r"(c2), "h"((uint16_t)3) : "memory");
}
__device__ __forceinline__ void bulk_g2s(uint32_t dst, const void* src, uint32_t bytes, uint32_t bar) {
  asm volatile("cp.async.bulk.shared::cluster.global.mbarrier::complete_tx::bytes [%0], [%1], %2, [%3];"
               ::"r"(dst), "l"(src), "r"(bytes), "r"(bar) : "memory");
}
__device__ __forceinline__ void prefetch_map(const CUtensorMap* m) {
  asm volatile("prefetch.tensormap [%0];" ::"l"(m) : "memory");
}
__device__ __forceinline__ void fence_proxy_async() { asm volatile("fence.proxy.async.global;" ::: "memory"); }
__device__ __forceinline__ void fence_proxy_smem() { asm volatile("fence.proxy.async.shared::cta;" ::: "memory"); }
__device__ __forceinline__ void wg_fence() { asm volatile("wgmma.fence.sync.aligned;" ::: "memory"); }
__device__ __forceinline__ void wg_commit() { asm volatile("wgmma.commit_group.sync.aligned;" ::: "memory"); }
template <int N> __device__ __forceinline__ void wg_wait() { asm volatile("wgmma.wait_group.sync.aligned %0;" ::"n"(N) : "memory"); }
__device__ __forceinline__ void bar_sync(int id, int n) { asm volatile("bar.sync %0, %1;" ::"r"(id), "r"(n) : "memory"); }
constexpr uint32_t SB0 = 1024;
__host__ __device__ constexpr uint32_t desc_lo(uint32_t off, uint32_t lbo) { return ((SB0 + off) >> 4) | ((lbo >> 4) << 16); }
__host__ __device__ constexpr uint32_t desc_hi(uint32_t sbo, uint32_t sw) { return (sbo >> 4) | (sw << 30); }
constexpr uint32_t HI_SW128 = desc_hi(1024, 1), HI_SW64 = desc_hi(512, 2), HI_NONE = desc_hi(128, 0);
__device__ __forceinline__ unsigned ld_acquire(const unsigned* p) {
  unsigned v;
  asm volatile("ld.acquire.gpu.global.u32 %0, [%1];" : "=r"(v) : "l"(p) : "memory");
  return v;
}
__device__ __forceinline__ void flag_wait(int idx, unsigned target) {
  const unsigned* p = &g_cnt[idx * 32];
  uint32_t it = 0;
  while ((int)(ld_acquire(p) - target) < 0) {
    if (++it > SPIN_LIMIT) __trap();
    __nanosleep(32);
  }
}
__device__ __forceinline__ void flag_signal(int idx) {
  asm volatile("red.release.gpu.global.add.u32 [%0], 1;" ::"l"(&g_cnt[idx * 32]) : "memory");
}
__device__ __forceinline__ unsigned read_epoch() {
  unsigned v;
  asm volatile("ld.relaxed.gpu.global.u32 %0, [%1];" : "=r"(v) : "l"(&g_cnt[C_DONE * 32]) : "memory");
  return v / NCTA + 1;
}
__device__ __forceinline__ uint32_t prmt(uint32_t a, uint32_t b, uint32_t s) { return __byte_perm(a, b, s); }
__device__ __forceinline__ uint32_t pack_bf16(float lo, float hi) {
  uint32_t r;
  asm("cvt.rn.bf16x2.f32 %0, %1, %2;" : "=r"(r) : "f"(hi), "f"(lo));
  return r;
}
__device__ __forceinline__ uint32_t bmul2(uint32_t a, uint32_t b) {
  uint32_t r;
  asm("mul.rn.bf16x2 %0, %1, %2;" : "=r"(r) : "r"(a), "r"(b));
  return r;
}
__device__ __forceinline__ uint32_t badd2(uint32_t a, uint32_t b) {
  uint32_t r;
  asm("add.rn.bf16x2 %0, %1, %2;" : "=r"(r) : "r"(a), "r"(b));
  return r;
}
__device__ __forceinline__ float bf_lo(uint32_t v) { return __uint_as_float(v << 16); }
__device__ __forceinline__ float bf_hi(uint32_t v) { return __uint_as_float(v & 0xFFFF0000u); }
__device__ __forceinline__ float bf_round(float f) { return __bfloat162float(__float2bfloat16_rn(f)); }
__device__ __forceinline__ uint4 ldg128(const void* p) {
  uint4 v;
  asm volatile("ld.global.nc.L1::no_allocate.v4.b32 {%0,%1,%2,%3}, [%4];" : "=r"(v.x), "=r"(v.y), "=r"(v.z), "=r"(v.w) : "l"(p));
  return v;
}
__device__ __forceinline__ uint32_t u4get(const uint4& v, int i) { return i == 0 ? v.x : i == 1 ? v.y : i == 2 ? v.z : v.w; }
__device__ __forceinline__ uint32_t lds32(uint32_t a) {
  uint32_t v;
  asm volatile("ld.shared.b32 %0, [%1];" : "=r"(v) : "r"(a) : "memory");
  return v;
}
__device__ __forceinline__ uint4 lds128(uint32_t a) {
  uint4 v;
  asm volatile("ld.shared.v4.b32 {%0,%1,%2,%3}, [%4];" : "=r"(v.x), "=r"(v.y), "=r"(v.z), "=r"(v.w) : "r"(a) : "memory");
  return v;
}
__device__ __forceinline__ void sts32(uint32_t a, uint32_t v) { asm volatile("st.shared.b32 [%0], %1;" ::"r"(a), "r"(v) : "memory"); }
__device__ __forceinline__ void sts128(uint32_t a, uint32_t x, uint32_t y, uint32_t z, uint32_t w) {
  asm volatile("st.shared.v4.b32 [%0], {%1,%2,%3,%4};" ::"r"(a), "r"(x), "r"(y), "r"(z), "r"(w) : "memory");
}
__device__ __forceinline__ void ldsm4(uint32_t a, uint32_t& r0, uint32_t& r1, uint32_t& r2, uint32_t& r3) {
  asm volatile("ldmatrix.sync.aligned.m8n8.x4.shared.b16 {%0,%1,%2,%3}, [%4];" : "=r"(r0), "=r"(r1), "=r"(r2), "=r"(r3) : "r"(a) : "memory");
}
__device__ __forceinline__ void ldsm4t(uint32_t a, uint32_t& r0, uint32_t& r1, uint32_t& r2, uint32_t& r3) {
  asm volatile("ldmatrix.sync.aligned.m8n8.x4.trans.shared.b16 {%0,%1,%2,%3}, [%4];" : "=r"(r0), "=r"(r1), "=r"(r2), "=r"(r3) : "r"(a) : "memory");
}
__device__ __forceinline__ float tanh_approx(float x) {
  float r;
  asm("tanh.approx.f32 %0, %1;" : "=f"(r) : "f"(x));
  return r;
}
__device__ __forceinline__ float geglu(float g, float u) {
  float t = g * fmaf(g * g, 0.0356774081f, 0.7978845608f);
  float hx = 0.5f * g * u;
  return fmaf(hx, tanh_approx(t), hx);
}

__device__ __forceinline__ void wgmma_ss_n128(float (&d)[64], uint32_t alo, uint32_t ahi, uint32_t blo, uint32_t bhi, int sd) {
  asm volatile("{\n.reg .pred p;\n.reg .b64 da, db;\nsetp.ne.b32 p, %68, 0;\nmov.b64 da, {%64, %65};\nmov.b64 db, {%66, %67};\n"
    "wgmma.mma_async.sync.aligned.m64n128k16.f32.bf16.bf16 {%0,%1,%2,%3,%4,%5,%6,%7,%8,%9,%10,%11,%12,%13,%14,%15,%16,%17,%18,%19,%20,%21,%22,%23,%24,%25,%26,%27,%28,%29,%30,%31,%32,%33,%34,%35,%36,%37,%38,%39,%40,%41,%42,%43,%44,%45,%46,%47,%48,%49,%50,%51,%52,%53,%54,%55,%56,%57,%58,%59,%60,%61,%62,%63}, da, db, p, 1, 1, 0, 1;\n}"
    : "+f"(d[0]),"+f"(d[1]),"+f"(d[2]),"+f"(d[3]),"+f"(d[4]),"+f"(d[5]),"+f"(d[6]),"+f"(d[7]),"+f"(d[8]),"+f"(d[9]),"+f"(d[10]),"+f"(d[11]),"+f"(d[12]),"+f"(d[13]),"+f"(d[14]),"+f"(d[15]),"+f"(d[16]),"+f"(d[17]),"+f"(d[18]),"+f"(d[19]),"+f"(d[20]),"+f"(d[21]),"+f"(d[22]),"+f"(d[23]),"+f"(d[24]),"+f"(d[25]),"+f"(d[26]),"+f"(d[27]),"+f"(d[28]),"+f"(d[29]),"+f"(d[30]),"+f"(d[31]),"+f"(d[32]),"+f"(d[33]),"+f"(d[34]),"+f"(d[35]),"+f"(d[36]),"+f"(d[37]),"+f"(d[38]),"+f"(d[39]),"+f"(d[40]),"+f"(d[41]),"+f"(d[42]),"+f"(d[43]),"+f"(d[44]),"+f"(d[45]),"+f"(d[46]),"+f"(d[47]),"+f"(d[48]),"+f"(d[49]),"+f"(d[50]),"+f"(d[51]),"+f"(d[52]),"+f"(d[53]),"+f"(d[54]),"+f"(d[55]),"+f"(d[56]),"+f"(d[57]),"+f"(d[58]),"+f"(d[59]),"+f"(d[60]),"+f"(d[61]),"+f"(d[62]),"+f"(d[63]) : "r"(alo), "r"(ahi), "r"(blo), "r"(bhi), "r"(sd));
}
__device__ __forceinline__ void wgmma_ss_n192(float (&d)[96], uint32_t alo, uint32_t ahi, uint32_t blo, uint32_t bhi, int sd) {
  asm volatile("{\n.reg .pred p;\n.reg .b64 da, db;\nsetp.ne.b32 p, %100, 0;\nmov.b64 da, {%96, %97};\nmov.b64 db, {%98, %99};\n"
    "wgmma.mma_async.sync.aligned.m64n192k16.f32.bf16.bf16 {%0,%1,%2,%3,%4,%5,%6,%7,%8,%9,%10,%11,%12,%13,%14,%15,%16,%17,%18,%19,%20,%21,%22,%23,%24,%25,%26,%27,%28,%29,%30,%31,%32,%33,%34,%35,%36,%37,%38,%39,%40,%41,%42,%43,%44,%45,%46,%47,%48,%49,%50,%51,%52,%53,%54,%55,%56,%57,%58,%59,%60,%61,%62,%63,%64,%65,%66,%67,%68,%69,%70,%71,%72,%73,%74,%75,%76,%77,%78,%79,%80,%81,%82,%83,%84,%85,%86,%87,%88,%89,%90,%91,%92,%93,%94,%95}, da, db, p, 1, 1, 0, 1;\n}"
    : "+f"(d[0]),"+f"(d[1]),"+f"(d[2]),"+f"(d[3]),"+f"(d[4]),"+f"(d[5]),"+f"(d[6]),"+f"(d[7]),"+f"(d[8]),"+f"(d[9]),"+f"(d[10]),"+f"(d[11]),"+f"(d[12]),"+f"(d[13]),"+f"(d[14]),"+f"(d[15]),"+f"(d[16]),"+f"(d[17]),"+f"(d[18]),"+f"(d[19]),"+f"(d[20]),"+f"(d[21]),"+f"(d[22]),"+f"(d[23]),"+f"(d[24]),"+f"(d[25]),"+f"(d[26]),"+f"(d[27]),"+f"(d[28]),"+f"(d[29]),"+f"(d[30]),"+f"(d[31]),"+f"(d[32]),"+f"(d[33]),"+f"(d[34]),"+f"(d[35]),"+f"(d[36]),"+f"(d[37]),"+f"(d[38]),"+f"(d[39]),"+f"(d[40]),"+f"(d[41]),"+f"(d[42]),"+f"(d[43]),"+f"(d[44]),"+f"(d[45]),"+f"(d[46]),"+f"(d[47]),"+f"(d[48]),"+f"(d[49]),"+f"(d[50]),"+f"(d[51]),"+f"(d[52]),"+f"(d[53]),"+f"(d[54]),"+f"(d[55]),"+f"(d[56]),"+f"(d[57]),"+f"(d[58]),"+f"(d[59]),"+f"(d[60]),"+f"(d[61]),"+f"(d[62]),"+f"(d[63]),"+f"(d[64]),"+f"(d[65]),"+f"(d[66]),"+f"(d[67]),"+f"(d[68]),"+f"(d[69]),"+f"(d[70]),"+f"(d[71]),"+f"(d[72]),"+f"(d[73]),"+f"(d[74]),"+f"(d[75]),"+f"(d[76]),"+f"(d[77]),"+f"(d[78]),"+f"(d[79]),"+f"(d[80]),"+f"(d[81]),"+f"(d[82]),"+f"(d[83]),"+f"(d[84]),"+f"(d[85]),"+f"(d[86]),"+f"(d[87]),"+f"(d[88]),"+f"(d[89]),"+f"(d[90]),"+f"(d[91]),"+f"(d[92]),"+f"(d[93]),"+f"(d[94]),"+f"(d[95]) : "r"(alo), "r"(ahi), "r"(blo), "r"(bhi), "r"(sd));
}
__device__ __forceinline__ void wgmma_rs_n64(float (&d)[32], uint32_t a0, uint32_t a1, uint32_t a2, uint32_t a3, uint32_t blo, uint32_t bhi, int sd) {
  asm volatile("{\n.reg .pred p;\n.reg .b64 db;\nsetp.ne.b32 p, %38, 0;\nmov.b64 db, {%36, %37};\n"
    "wgmma.mma_async.sync.aligned.m64n64k16.f32.bf16.bf16 {%0,%1,%2,%3,%4,%5,%6,%7,%8,%9,%10,%11,%12,%13,%14,%15,%16,%17,%18,%19,%20,%21,%22,%23,%24,%25,%26,%27,%28,%29,%30,%31}, {%32,%33,%34,%35}, db, p, 1, 1, 0;\n}"
    : "+f"(d[0]),"+f"(d[1]),"+f"(d[2]),"+f"(d[3]),"+f"(d[4]),"+f"(d[5]),"+f"(d[6]),"+f"(d[7]),"+f"(d[8]),"+f"(d[9]),"+f"(d[10]),"+f"(d[11]),"+f"(d[12]),"+f"(d[13]),"+f"(d[14]),"+f"(d[15]),"+f"(d[16]),"+f"(d[17]),"+f"(d[18]),"+f"(d[19]),"+f"(d[20]),"+f"(d[21]),"+f"(d[22]),"+f"(d[23]),"+f"(d[24]),"+f"(d[25]),"+f"(d[26]),"+f"(d[27]),"+f"(d[28]),"+f"(d[29]),"+f"(d[30]),"+f"(d[31]) : "r"(a0), "r"(a1), "r"(a2), "r"(a3), "r"(blo), "r"(bhi), "r"(sd));
}
__device__ __forceinline__ void wgmma_rs_n128(float (&d)[64], uint32_t a0, uint32_t a1, uint32_t a2, uint32_t a3, uint32_t blo, uint32_t bhi, int sd) {
  asm volatile("{\n.reg .pred p;\n.reg .b64 db;\nsetp.ne.b32 p, %70, 0;\nmov.b64 db, {%68, %69};\n"
    "wgmma.mma_async.sync.aligned.m64n128k16.f32.bf16.bf16 {%0,%1,%2,%3,%4,%5,%6,%7,%8,%9,%10,%11,%12,%13,%14,%15,%16,%17,%18,%19,%20,%21,%22,%23,%24,%25,%26,%27,%28,%29,%30,%31,%32,%33,%34,%35,%36,%37,%38,%39,%40,%41,%42,%43,%44,%45,%46,%47,%48,%49,%50,%51,%52,%53,%54,%55,%56,%57,%58,%59,%60,%61,%62,%63}, {%64,%65,%66,%67}, db, p, 1, 1, 0;\n}"
    : "+f"(d[0]),"+f"(d[1]),"+f"(d[2]),"+f"(d[3]),"+f"(d[4]),"+f"(d[5]),"+f"(d[6]),"+f"(d[7]),"+f"(d[8]),"+f"(d[9]),"+f"(d[10]),"+f"(d[11]),"+f"(d[12]),"+f"(d[13]),"+f"(d[14]),"+f"(d[15]),"+f"(d[16]),"+f"(d[17]),"+f"(d[18]),"+f"(d[19]),"+f"(d[20]),"+f"(d[21]),"+f"(d[22]),"+f"(d[23]),"+f"(d[24]),"+f"(d[25]),"+f"(d[26]),"+f"(d[27]),"+f"(d[28]),"+f"(d[29]),"+f"(d[30]),"+f"(d[31]),"+f"(d[32]),"+f"(d[33]),"+f"(d[34]),"+f"(d[35]),"+f"(d[36]),"+f"(d[37]),"+f"(d[38]),"+f"(d[39]),"+f"(d[40]),"+f"(d[41]),"+f"(d[42]),"+f"(d[43]),"+f"(d[44]),"+f"(d[45]),"+f"(d[46]),"+f"(d[47]),"+f"(d[48]),"+f"(d[49]),"+f"(d[50]),"+f"(d[51]),"+f"(d[52]),"+f"(d[53]),"+f"(d[54]),"+f"(d[55]),"+f"(d[56]),"+f"(d[57]),"+f"(d[58]),"+f"(d[59]),"+f"(d[60]),"+f"(d[61]),"+f"(d[62]),"+f"(d[63]) : "r"(a0), "r"(a1), "r"(a2), "r"(a3), "r"(blo), "r"(bhi), "r"(sd));
}

__device__ __forceinline__ void bar_arrive(int id, int n) { asm volatile("bar.arrive %0, %1;" ::"r"(id), "r"(n) : "memory"); }
__device__ __forceinline__ void mbar_arrive(uint32_t bar) {
  asm volatile("mbarrier.arrive.shared::cta.b64 _, [%0];" ::"r"(bar) : "memory");
}
__host__ __device__ constexpr uint32_t wslot(int r) { return (uint32_t)(8 + r); }
__host__ __device__ constexpr uint32_t doff2(int i) { return (uint32_t)i * 24576u; }
__host__ __device__ constexpr uint32_t hoff(int i) { return (uint32_t)i * 24576u + 16384u; }
__device__ __forceinline__ uint32_t slot_free_bar(uint32_t bars, int k) { return bars + 8 * (k < 8 ? B_XEMPTY + k : B_WLAST + k - 6); }

__device__ __forceinline__ void store_quad(__nv_bfloat16* rowp, int U, int t, uint32_t v0, uint32_t v1, uint32_t v2, uint32_t v3) {
  const bool odd = t & 1, up = t & 2;
  const uint32_t r0 = __shfl_xor_sync(0xffffffffu, odd ? v0 : v1, 1);
  const uint32_t r1 = __shfl_xor_sync(0xffffffffu, odd ? v2 : v3, 1);
  const uint32_t a0 = odd ? r0 : v0, a1 = odd ? v1 : r0, b0 = odd ? r1 : v2, b1 = odd ? v3 : r1;
  const uint32_t s0 = __shfl_xor_sync(0xffffffffu, up ? a0 : b0, 2);
  const uint32_t s1 = __shfl_xor_sync(0xffffffffu, up ? a1 : b1, 2);
  const uint4 o = up ? make_uint4(s0, s1, b0, b1) : make_uint4(a0, a1, s0, s1);
  *reinterpret_cast<uint4*>(rowp + 32 * U + 8 * t) = o;
}

template <int U, int R, int UO, int N>
__device__ __forceinline__ void geglu_unit(const float (&a)[N], __nv_bfloat16* h0, int t) {
  constexpr int i0 = 16 * U + 2 * R;
  const uint32_t v0 = pack_bf16(geglu(a[i0 + 0], a[UO + i0 + 0]), geglu(a[i0 + 1], a[UO + i0 + 1]));
  const uint32_t v1 = pack_bf16(geglu(a[i0 + 4], a[UO + i0 + 4]), geglu(a[i0 + 5], a[UO + i0 + 5]));
  const uint32_t v2 = pack_bf16(geglu(a[i0 + 8], a[UO + i0 + 8]), geglu(a[i0 + 9], a[UO + i0 + 9]));
  const uint32_t v3 = pack_bf16(geglu(a[i0 + 12], a[UO + i0 + 12]), geglu(a[i0 + 13], a[UO + i0 + 13]));
  store_quad(h0 + (size_t)(8 * R) * F_DIM, U, t, v0, v1, v2, v3);
}

__device__ __forceinline__ void g2_chunk(float (&acc)[64], uint32_t bars, int st, int par, int sd) {
  mbar_wait(bars + 8 * (B_GFULL + st), par);
  const uint32_t da = desc_lo(hoff(st), 16);
  const uint32_t db = desc_lo(doff2(st), 8192);
  wg_fence();
#pragma unroll
  for (int k = 0; k < 4; k++) wgmma_ss_n128(acc, da + 2 * k, HI_SW128, db + 128 * k, HI_SW128, k ? 1 : sd);
  wg_commit();
}

template <int G>
__device__ __forceinline__ void conv_lda(uint32_t (&ar)[16], uint32_t abase) {
#pragma unroll
  for (int i = 0; i < 4; i++) {
    const uint32_t a = abase - 1024 * (G >> 1) - 128 * (G & 1) - 32 * i;
    ar[4 * i + 0] = lds32(a);
    ar[4 * i + 1] = lds32(a - 512);
    ar[4 * i + 2] = lds32(a + 16);
    ar[4 * i + 3] = lds32(a - 496);
  }
}
template <int G>
__device__ __forceinline__ void conv_issue(float (&cf)[64], float (&cs)[32], const uint32_t (&ar)[16], uint32_t dsc) {
  wg_fence();
#pragma unroll
  for (int i = 0; i < 4; i++) {
    const uint32_t d = dsc + 32 * (G >> 1) + 4 * (G & 1) + i;
    if (G < 4) wgmma_rs_n128(cf, ar[4 * i], ar[4 * i + 1], ar[4 * i + 2], ar[4 * i + 3], d, HI_NONE, 1);
    else wgmma_rs_n64(cs, ar[4 * i], ar[4 * i + 1], ar[4 * i + 2], ar[4 * i + 3], d, HI_NONE, (G == 4 && i == 0) ? 0 : 1);
  }
  wg_commit();
}
__device__ __forceinline__ void conv_fin(uint32_t yaddr, bool hi, bool qodd, float v00, float v01, float v10, float v11, float v20, float v21) {
  const float y0 = (hi ? v20 : v00) + __shfl_xor_sync(0xffffffffu, v10, 16);
  const float y1 = (hi ? v21 : v01) + __shfl_xor_sync(0xffffffffu, v11, 16);
  const float r = __shfl_xor_sync(0xffffffffu, qodd ? y0 : y1, 4);
  sts32(yaddr, qodd ? pack_bf16(r, y1) : pack_bf16(y0, r));
}
__device__ __forceinline__ void gate_rows(uint32_t sb, uint32_t bars, const __nv_bfloat16* gate_w, int row0, int grow0, int lane) {
  const uint4 w0 = ldg128(reinterpret_cast<const uint4*>(gate_w) + lane);
  const uint4 w1 = ldg128(reinterpret_cast<const uint4*>(gate_w) + 32 + lane);
#pragma unroll 1
  for (int c = 0; c < 8; c++) mbar_wait(bars + 8 * (B_XFULL + c), 0);
  float mine = 0.f;
#pragma unroll 2
  for (int i = 0; i < 8; i++) {
    const uint32_t a = sb + (lane >> 3) * SLOT + (row0 + i) * 128 + (((lane & 7) ^ i) << 4);
    const uint4 x0 = lds128(a), x1 = lds128(a + 4 * SLOT);
    const uint32_t p[8] = {bmul2(x0.x, w0.x), bmul2(x0.y, w0.y), bmul2(x0.z, w0.z), bmul2(x0.w, w0.w),
                           bmul2(x1.x, w1.x), bmul2(x1.y, w1.y), bmul2(x1.z, w1.z), bmul2(x1.w, w1.w)};
    float s = ((bf_lo(p[0]) + bf_hi(p[0])) + (bf_lo(p[1]) + bf_hi(p[1]))) + ((bf_lo(p[2]) + bf_hi(p[2])) + (bf_lo(p[3]) + bf_hi(p[3]))) +
              ((bf_lo(p[4]) + bf_hi(p[4])) + (bf_lo(p[5]) + bf_hi(p[5]))) + ((bf_lo(p[6]) + bf_hi(p[6])) + (bf_lo(p[7]) + bf_hi(p[7])));
#pragma unroll
    for (int o = 16; o > 0; o >>= 1) s += __shfl_xor_sync(0xffffffffu, s, o);
    if (lane == i) mine = s;
  }
  if (lane < 8) {
    mbar_arrive_both(bars + 8 * (B_XEMPTY + lane));
    g_gate[grow0 + lane] = bf_round(1.0f / (1.0f + __expf(-bf_round(mine))));
  }
  fence_proxy_async();
  __syncwarp();
  if (lane == 0) flag_signal(C_PRE);
}
__device__ __forceinline__ void conv_fetch(uint32_t sb, uint32_t bars, const __nv_bfloat16* ssm_k, int ch, int c, int part) {
  const uint32_t fb = bars + 8 * (B_CFULL + c);
  const uint32_t bytes = part ? 2048 : 4096;
  const uint32_t dst = part ? sb + CV_U + (c & 1) * CV_UCH + (part - 1) * CV_UHALF : sb + CV_HRAW + 16;
  const void* src = part ? (const void*)(g_u + ch * 256 + (part - 1) * 128) : (const void*)(ssm_k + (size_t)ch * S_LEN);
  mbar_expect(fb, bytes);
  bulk_g2s(dst, src, bytes, fb);
}
__device__ __forceinline__ void conv_build_h(uint32_t xb, const uint4& hw0, const uint4& hw1, uint32_t hprev) {
  sts128(xb + CV_HCOPY, prmt(hw1.w, 0, 0x1032), prmt(hw1.z, 0, 0x1032), prmt(hw1.y, 0, 0x1032), prmt(hw1.x, 0, 0x1032));
  sts128(xb + CV_HCOPY + 16, prmt(hw0.w, 0, 0x1032), prmt(hw0.z, 0, 0x1032), prmt(hw0.y, 0, 0x1032), prmt(hw0.x, 0, 0x1032));
  sts128(xb, prmt(hw1.w, hw1.z, 0x7610), prmt(hw1.z, hw1.y, 0x7610), prmt(hw1.y, hw1.x, 0x7610), prmt(hw1.x, hw0.w, 0x7610));
  sts128(xb + 16, prmt(hw0.w, hw0.z, 0x7610), prmt(hw0.z, hw0.y, 0x7610), prmt(hw0.y, hw0.x, 0x7610), prmt(hw0.x, hprev, 0x5410));
}

__global__ void __cluster_dims__(2, 1, 1) __launch_bounds__(NTHREADS, 1)
fused_kernel(const __grid_constant__ Maps maps, const __nv_bfloat16* __restrict__ q, const __nv_bfloat16* __restrict__ kin,
             const __nv_bfloat16* __restrict__ vin, const __nv_bfloat16* __restrict__ shift_k,
             const __nv_bfloat16* __restrict__ ssm_k, const __nv_bfloat16* __restrict__ ssm_D,
             const __nv_bfloat16* __restrict__ gate_w, __nv_bfloat16* __restrict__ out) {
  extern __shared__ uint8_t smem_raw[];
  uint32_t sb;
  asm volatile("mov.u32 %0, %1;" : "=r"(sb) : "r"((s2u(smem_raw) + 1023u) & ~1023u));
  if ((sb & 0xFFFFFFu) != SB0) __trap();
  const uint32_t bars = sb + OFF_BAR;
  const int warp = __shfl_sync(0xffffffffu, (int)(threadIdx.x >> 5), 0), lane = threadIdx.x & 31;
  const int b = blockIdx.x;
  const int rank = b & 1, pair = b >> 1;
  const int f = pair & 7, m1 = 2 * (pair >> 3) + rank;
  const int m2 = pair >> 2, r2 = 2 * m2 + rank, cb = pair & 3;

  if (lane == 0) {
    if (warp < 9) prefetch_map(reinterpret_cast<const CUtensorMap*>(&maps) + warp);
#pragma unroll
    for (int k = 0; k < 4; k++) {
      const int i = 4 * warp + k;
      int cnt = 1;
      if (i >= B_XEMPTY && i < B_WFULL) cnt = 8;
      else if (i >= B_WEMPTY && i < B_GFULL) cnt = 4;
      else if (i >= B_GEMPTY && i < B_QFULL) cnt = 2;
      else if (i >= B_CFULL && i < B_HRDY) cnt = 3;
      mbar_init(bars + 8 * i, cnt);
    }
    asm volatile("fence.mbarrier_init.release.cluster;" ::: "memory");
    fence_proxy_smem();
  }
  if (threadIdx.x == 0) PROF(56);
  __syncthreads();
  asm volatile("barrier.cluster.arrive.relaxed.aligned;" ::: "memory");
  if (threadIdx.x == 384) {
    mbar_expect(bars + 8 * B_XFULL, SLOT);
    tma2d(sb, &maps.x, 0, 128 * m1, bars + 8 * B_XFULL);
  }
  __syncwarp();
  asm volatile("barrier.cluster.wait.aligned;" ::: "memory");
  if (threadIdx.x == 0) PROF(58);

  if (warp < 8) {
    asm volatile("setmaxnreg.inc.sync.aligned.u32 160;");
    const int wg = warp >> 2, wl = warp & 3, g = lane >> 2, t = lane & 3;
    const bool elect = (threadIdx.x & 127) == 0;
    const float nz = __uint_as_float(0x80000000u | (uint32_t)(blockIdx.y));
    const uint32_t dxa = desc_lo(wg * 8192, 16);
    __nv_bfloat16* hrow = g_H + (size_t)(128 * m1 + 64 * wg + 16 * wl + g) * F_DIM;
    __nv_bfloat16* hlast;
    float old[64];
    if (elect) PROF(0 + 16 * wg);
    {
      float a0[96];
      int r = 0, par = 0, prev = 0;
#pragma unroll 1
      for (int c = 0; c < 8; c++) {
        mbar_wait(bars + 8 * (B_XFULL + c), 0);
#pragma unroll
        for (int h = 0; h < 2; h++) {
          mbar_wait(bars + 8 * (B_WFULL + r), par);
          const uint32_t db = desc_lo(wslot(r) * SLOT, 2048);
          wg_fence();
          wgmma_ss_n192(a0, dxa + c * 1024 + 4 * h, HI_SW128, db, HI_SW64, (c | h) != 0);
          wgmma_ss_n192(a0, dxa + c * 1024 + 4 * h + 2, HI_SW128, db + 64, HI_SW64, 1);
          wg_commit();
          wg_wait<1>();
          if (elect && (c | h) != 0) mbar_arrive_both(bars + 8 * (B_WEMPTY + prev));
          prev = (c == 5) ? (B_WLAST - B_WEMPTY + h) : r;
          if (++r == 6) { r = 0; par ^= 1; }
        }
      }
      wg_wait<0>();
      if (elect) mbar_arrive_both(bars + 8 * (B_WEMPTY + prev));
      if (elect) PROF(2 + 16 * wg);
      geglu_unit<2, 0, 48>(a0, hrow + 96 * f, t);
      geglu_unit<2, 1, 48>(a0, hrow + 96 * f, t);
#pragma unroll
      for (int i = 0; i < 32; i++) { old[i] = a0[i] + nz; old[32 + i] = a0[48 + i] + nz; }
    }
    {
      if (elect) PROF(1 + 16 * wg);
      __nv_bfloat16* hout = hrow + 96 * f;
#pragma unroll 1
      for (int j = 1; j < 3; j++) {
        float acc[64];
#pragma unroll
        for (int s = 0; s < 8; s++) {
          mbar_wait(bars + 8 * (B_WFULL + (s & 3)), ((s >> 2) & 1) ^ 1);
          PROFX(160 + 8 * (j - 1) + s, threadIdx.x == 0);
          const uint32_t db = desc_lo(wslot(s & 3) * SLOT, 4096);
          wg_fence();
#pragma unroll
          for (int k = 0; k < 4; k++) wgmma_ss_n128(acc, dxa + s * 1024 + 2 * k, HI_SW128, db + 64 * k, HI_SW64, (s | k) != 0);
          wg_commit();
          if (s > 0) {
            wg_wait<1>();
            if (elect) {
              mbar_arrive_both(bars + 8 * ((j == 2 && s >= 5) ? (B_WLAST + s - 3) : (B_WEMPTY + ((s - 1) & 3))));
              if (j == 2) mbar_arrive_both(bars + 8 * (B_XEMPTY + s - 1));
            }
          }
          if (s == 0) geglu_unit<0, 0, 32>(old, hout, t);
          if (s == 1) geglu_unit<0, 1, 32>(old, hout, t);
          if (s == 3) geglu_unit<1, 0, 32>(old, hout, t);
          if (s == 5) {
            geglu_unit<1, 1, 32>(old, hout, t);
            fence_proxy_async();
            bar_arrive(4 + j - 1, 288);
          }
        }
        wg_wait<0>();
        if (elect) {
          mbar_arrive_both(bars + 8 * (j == 2 ? (B_WLAST + 5) : (B_WEMPTY + 3)));
          if (j == 2) mbar_arrive_both(bars + 8 * (B_XEMPTY + 7));
        }
#pragma unroll
        for (int i = 0; i < 64; i++) old[i] = acc[i] + nz;
        hout = hrow + 256 + 512 * j + 64 * f;
        if (elect) PROF(2 + j + 16 * wg);
      }
      hlast = hout;
    }
    float acc[64];
    {
      g2_chunk(acc, bars, wg, 0, 0);
      geglu_unit<0, 0, 32>(old, hlast, t);
      geglu_unit<0, 1, 32>(old, hlast, t);
      g2_chunk(acc, bars, wg + 2, 0, 1);
      geglu_unit<1, 0, 32>(old, hlast, t);
      geglu_unit<1, 1, 32>(old, hlast, t);
      fence_proxy_async();
      bar_arrive(6, 288);
      if (elect) PROF(7 + 16 * wg);
      wg_wait<1>();
      if (elect) mbar_arrive_both(bars + 8 * (B_GEMPTY + wg));
      int st = wg + 4, par = 0, prev = wg + 2;
#pragma unroll 1
      for (int kk = 2; kk < 14; kk++) {
        if (kk == YIELD1) mbar_wait(bars + 8 * (B_CDONE + 1), 0);
        if (kk == YIELD2) mbar_wait(bars + 8 * (B_CDONE + 2), 0);
        g2_chunk(acc, bars, st, par, 1);
        if (elect) PROF(64 + 2 * kk + wg);
        wg_wait<1>();
        if (elect) mbar_arrive_both(bars + 8 * (B_GEMPTY + prev));
        prev = st;
        st += 2;
        if (st >= GRING) { st -= GRING; par ^= 1; }
      }
      wg_wait<0>();
    }
    if (elect) PROF(11 + 16 * wg);
    {
      const uint32_t tl = (threadIdx.x & 127) * 16;
      #pragma unroll
      for (int i = 0; i < 8; i++) {
        const int e = 4 * i;
        if (wg == 0) sts128(sb + doff2(6) + i * 2048 + tl, __float_as_uint(acc[32 + e]), __float_as_uint(acc[33 + e]), __float_as_uint(acc[34 + e]), __float_as_uint(acc[35 + e]));
        else sts128(sb + doff2(7) + i * 2048 + tl, __float_as_uint(acc[e]), __float_as_uint(acc[1 + e]), __float_as_uint(acc[2 + e]), __float_as_uint(acc[3 + e]));
      }
      bar_sync(9, 256);
#pragma unroll
      for (int i = 0; i < 8; i++) {
        const uint4 v = lds128(sb + doff2(7 - wg) + i * 2048 + tl);
        const int e = 4 * i;
        old[e + 0] = (wg ? acc[32 + e] : acc[e]) + __uint_as_float(v.x);
        old[e + 1] = (wg ? acc[33 + e] : acc[1 + e]) + __uint_as_float(v.y);
        old[e + 2] = (wg ? acc[34 + e] : acc[2 + e]) + __uint_as_float(v.z);
        old[e + 3] = (wg ? acc[35 + e] : acc[3 + e]) + __uint_as_float(v.w);
      }
    }
    mbar_wait(bars + 8 * B_QFULL, 0);
    {
      const int r0 = 16 * wl + g;
      const float g0 = __uint_as_float(lds32(sb + OFF_GATE + 4 * r0));
      const float g1 = __uint_as_float(lds32(sb + OFF_GATE + 4 * (r0 + 8)));
      const uint32_t g0p = pack_bf16(g0, g0), g1p = pack_bf16(g1, g1);
      const uint32_t o0p = pack_bf16(1.0f - g0, 1.0f - g0), o1p = pack_bf16(1.0f - g1, 1.0f - g1);
      const int mi = lane >> 3, l7 = lane & 7;
      const int qrow = 16 * wl + l7 + 8 * (mi & 1);
      const uint32_t qaddr = sb + doff2(4) + wg * 8192 + qrow * 128;
      const int ych = 8 * (mi >> 1) + l7;
      const uint32_t yaddr = sb + doff2(5) + wg * 8192 + ych * 128 + (((2 * wl + (mi & 1)) ^ l7) << 4);
      __nv_bfloat16* o0 = out + (size_t)(64 * r2 + r0) * D_DIM + 128 * cb + 64 * wg;
      __nv_bfloat16* o1 = o0 + 8 * D_DIM;
      uint32_t qf[16], ob[16];
#pragma unroll
      for (int jj = 0; jj < 8; jj += 2) {
        ldsm4(qaddr + (((jj + (mi >> 1)) ^ l7) << 4), qf[2 * jj], qf[2 * jj + 1], qf[2 * jj + 2], qf[2 * jj + 3]);
#pragma unroll
        for (int i = 0; i < 4; i++) ob[2 * jj + i] = bmul2((i & 1) ? o1p : o0p, pack_bf16(old[4 * jj + 2 * i], old[4 * jj + 2 * i + 1]));
      }
      mbar_wait(bars + 8 * B_YFULL, 0);
      if (elect) PROF(12 + 16 * wg);
#pragma unroll
      for (int jj = 0; jj < 8; jj += 2) {
        uint32_t y[4];
        ldsm4t(yaddr + jj * 1024, y[0], y[1], y[2], y[3]);
#pragma unroll
        for (int i = 0; i < 4; i++) ob[2 * jj + i] = badd2(bmul2((i & 1) ? g1p : g0p, bmul2(qf[2 * jj + i], y[i])), ob[2 * jj + i]);
      }
#pragma unroll
      for (int U = 0; U < 2; U++) {
        store_quad(o0, U, t, ob[8 * U], ob[8 * U + 2], ob[8 * U + 4], ob[8 * U + 6]);
        store_quad(o1, U, t, ob[8 * U + 1], ob[8 * U + 3], ob[8 * U + 5], ob[8 * U + 7]);
      }
    }
    if (elect) PROF(13 + 16 * wg);
    asm volatile("barrier.cluster.arrive.relaxed.aligned;\nbarrier.cluster.wait.aligned; // gemm" ::: "memory");
    if (threadIdx.x == 0) { PROF(14); PROFG(62); }
    if (threadIdx.x == 0) atomicAdd(&g_cnt[C_DONE * 32], 1u);
  } else if (warp < 12) {
    asm volatile("setmaxnreg.inc.sync.aligned.u32 152;");
    const int tid = threadIdx.x - 256, wl = warp - 8, g = lane >> 2, t = lane & 3;
    if (tid == 0) PROF(32);
    {
      const int c0 = 64 * (b & 7) + 8 * ((lane >> 3) + 4 * (wl >> 1)), half = wl & 1;
      const int sblk = 128 * (b >> 3) + 16 * (lane & 7), s0 = sblk + 8 * half;
      const __nv_bfloat16* kp = kin + (size_t)s0 * D_DIM + c0;
      const __nv_bfloat16* vp = vin + (size_t)s0 * D_DIM + c0;
      uint4 kr[11], vr[8], sk[4];
#pragma unroll
      for (int r = 0; r < 11; r++) kr[r] = (r >= 3 || s0 > 0) ? ldg128(kp + (r - 3) * D_DIM) : make_uint4(0, 0, 0, 0);
#pragma unroll
      for (int r = 0; r < 8; r++) vr[r] = ldg128(vp + r * D_DIM);
#pragma unroll
      for (int i = 0; i < 4; i++) sk[i] = ldg128(shift_k + 4 * c0 + 8 * i);
      PROFX(176, tid == 0);
      PROFX(177, tid == 0 && (kr[10].x ^ kr[3].y ^ kr[0].z) != 0x12345);
      PROFX(178, tid == 0 && (vr[7].x ^ vr[0].y ^ sk[3].z) != 0x12345);
      uint4* up = g_u + c0 * 256 + half * 128 + (127 - (sblk >> 4));
#pragma unroll
      for (int i = 0; i < 4; i++) {
        const uint32_t sk0 = prmt(sk[i].x, sk[i].z, 0x5410), sk1 = prmt(sk[i].x, sk[i].z, 0x7632);
        const uint32_t sk2 = prmt(sk[i].y, sk[i].w, 0x5410), sk3 = prmt(sk[i].y, sk[i].w, 0x7632);
        uint32_t o[8];
#pragma unroll
        for (int r = 0; r < 8; r++) {
          uint32_t a = bmul2(u4get(kr[r], i), sk3);
          a = badd2(a, bmul2(u4get(kr[r + 1], i), sk2));
          a = badd2(a, bmul2(u4get(kr[r + 2], i), sk1));
          a = badd2(a, bmul2(u4get(kr[r + 3], i), sk0));
          o[r] = bmul2(a, u4get(vr[r], i));
        }
        up[(2 * i) * 256] = make_uint4(prmt(o[0], o[1], 0x5410), prmt(o[2], o[3], 0x5410), prmt(o[4], o[5], 0x5410), prmt(o[6], o[7], 0x5410));
        up[(2 * i + 1) * 256] = make_uint4(prmt(o[0], o[1], 0x7632), prmt(o[2], o[3], 0x7632), prmt(o[4], o[5], 0x7632), prmt(o[6], o[7], 0x7632));
      }
      PROFX(179, tid == 0);
      fence_proxy_async();
      bar_arrive(8, 160);
      if (tid == 0) PROF(33);
    }
    const int ch0 = 4 * b;
    const uint2 dall = *reinterpret_cast<const uint2*>(ssm_D + ch0);
    mbar_wait(bars + 8 * (B_WLAST + 0), 0);
    mbar_wait(bars + 8 * (B_WLAST + 1), 0);
    if (lane == 0 && wl < 3) {
      if (wl > 0) {
        flag_wait(C_PREU + (b >> 4), read_epoch() * 16);
        fence_proxy_async();
      }
      conv_fetch(sb, bars, ssm_k, 4 * b, 0, wl);
      if (wl == 1) PROF(35);
    }
    {
      const int arr = tid >> 5, r = tid & 31;
      sts128(sb + CV_U + arr * CV_UHALF + 2048 + r * 16, 0, 0, 0, 0);
      if (r < 24) sts128(sb + CV_U + arr * CV_UHALF + 2048 + 512 + r * 16, 0, 0, 0, 0);
      else if (r == 24) sts128(sb + CV_H + (arr >> 1) * CV_HCOPY + 4096 + (arr & 1) * 16, 0, 0, 0, 0);
      else if (r == 25) sts128(sb + CV_HRAW, 0, 0, 0, 0);
    }
    fence_proxy_smem();
    const bool hi = g >> 2, qodd = g & 1;
    const int rho = 4 * wl + (g & 3);
    const uint32_t abase = sb + CV_H + (g & 1) * CV_HCOPY + 2 * ((2046 + (g & 1)) - (rho + 128 * (g >> 2)) + 2 * t);
    const uint32_t yst = sb + CV_Y + 4 * (8 * (127 - (8 * (g >> 2) + 2 * t + (g & 1))) + 2 * wl + ((g >> 1) & 1));
    const uint32_t dm0 = hi ? 0u : (rho == 2 * t ? 0xFFFFu : rho == 2 * t + 1 ? 0xFFFF0000u : 0u);
    const uint32_t dm2 = hi ? 0u : (rho == 2 * t + 8 ? 0xFFFFu : rho == 2 * t + 9 ? 0xFFFF0000u : 0u);
    bar_sync(3, 128);
#pragma unroll 1
    for (int cp = 0; cp < 4; cp += 2)
#pragma unroll
    for (int buf = 0; buf < 2; buf++) {
      const int c = cp + buf;
      mbar_wait(bars + 8 * (B_CFULL + c), 0);
      {
        const uint32_t hr = sb + CV_HRAW + 16 + 32 * tid;
        const uint4 hw0 = lds128(hr), hw1 = lds128(hr + 16);
        conv_build_h(sb + CV_H + 2 * (2032 - 16 * tid), hw0, hw1, lds32(hr - 4) >> 16);
      }
      if (tid == 96) asm volatile("cp.async.bulk.wait_group.read 1;" ::: "memory");
      bar_sync(3, 128);
      if (lane == 0 && wl < 3 && c < 3) conv_fetch(sb, bars, ssm_k, ch0 + c + 1, c + 1, wl);
      __syncwarp();
      if (tid == 0) PROF(37 + 3 * c);
      const uint32_t dsc = desc_lo(CV_U + buf * CV_UCH, CV_UHALF);
      const uint32_t ya = yst + buf * 4096;
      float cf[64], cs[32];
      uint32_t ra[16], rb[16], rc[16];
      conv_lda<0>(ra, abase);
      {
        const uint32_t d2 = prmt((c & 2) ? dall.y : dall.x, 0, (c & 1) ? 0x3232 : 0x1010);
        rc[0] = d2 & dm0; rc[1] = 0; rc[2] = d2 & dm2; rc[3] = 0;
        wg_fence();
        wgmma_rs_n128(cf, rc[0], rc[1], rc[2], rc[3], dsc, HI_NONE, 0);
      }
      conv_issue<0>(cf, cs, ra, dsc);
      conv_lda<1>(rb, abase);
      conv_issue<1>(cf, cs, rb, dsc);
      wg_wait<1>();
      conv_lda<2>(ra, abase);
      conv_issue<2>(cf, cs, ra, dsc);
      wg_wait<1>();
      conv_lda<3>(rb, abase);
      conv_issue<3>(cf, cs, rb, dsc);
      wg_wait<1>();
      conv_lda<4>(ra, abase);
      wg_wait<0>();
      float v[17][2];
#pragma unroll
      for (int jj = 0; jj < 16; jj++)
#pragma unroll
        for (int e = 0; e < 2; e++) v[jj][e] = jj < 14 ? cf[4 * jj + e] + cf[4 * (jj + 2) + 2 + e] : cf[4 * jj + e];
      v[16][0] = v[16][1] = 0.f;
      conv_issue<4>(cf, cs, ra, dsc);
#pragma unroll
      for (int m = 4; m < 8; m++)
        conv_fin(ya - 512 * m, hi, qodd, v[2 * m][0], v[2 * m][1], v[2 * m + 1][0], v[2 * m + 1][1], v[2 * m + 2][0], v[2 * m + 2][1]);
      conv_lda<5>(rb, abase);
      conv_issue<5>(cf, cs, rb, dsc);
      conv_lda<6>(rc, abase);
      conv_issue<6>(cf, cs, rc, dsc);
      wg_wait<2>();
      conv_lda<7>(ra, abase);
      conv_issue<7>(cf, cs, ra, dsc);
      wg_wait<0>();
      if (tid == 0) PROF(38 + 3 * c);
#pragma unroll
      for (int jj = 0; jj < 8; jj++)
#pragma unroll
        for (int e = 0; e < 2; e++) v[jj][e] += jj < 6 ? cs[4 * jj + e] + cs[4 * (jj + 2) + 2 + e] : cs[4 * jj + e];
#pragma unroll
      for (int m = 0; m < 4; m++)
        conv_fin(ya - 512 * m, hi, qodd, v[2 * m][0], v[2 * m][1], v[2 * m + 1][0], v[2 * m + 1][1], v[2 * m + 2][0], v[2 * m + 2][1]);
      fence_proxy_smem();
      bar_sync(3, 128);
      if (tid == 64) mbar_arrive(bars + 8 * (B_CDONE + c));
      if (tid == 96 && c < 3) {
        asm volatile("cp.async.bulk.global.shared::cta.bulk_group [%0], [%1], 4096;"
                     ::"l"(g_yT + (ch0 + c) * S_LEN), "r"(sb + CV_Y + buf * 4096) : "memory");
        asm volatile("cp.async.bulk.commit_group;" ::: "memory");
      }
      if (tid == 96) PROF(39 + 3 * c);
    }
    {
      uint4* yp = reinterpret_cast<uint4*>(g_yT + (ch0 + 3) * S_LEN);
      yp[tid] = lds128(sb + CV_Y + 4096 + 16 * tid);
      yp[tid + 128] = lds128(sb + CV_Y + 4096 + 2048 + 16 * tid);
      if (tid == 96) asm volatile("cp.async.bulk.wait_group 0;" ::: "memory");
      fence_proxy_async();
      bar_sync(3, 128);
      if (tid == 96) flag_signal(C_CONV + (b >> 5));
    }
    if (tid == 96) PROF(49);
    asm volatile("barrier.cluster.arrive.relaxed.aligned;\nbarrier.cluster.wait.aligned; // conv" ::: "memory");
  } else {
    asm volatile("setmaxnreg.dec.sync.aligned.u32 40;");
    if (warp == 12) {
      if (lane == 0) {
        const CUtensorMap* m0p = rank ? &maps.wu0 : &maps.wg0;
        const CUtensorMap* m1p = rank ? &maps.wu1 : &maps.wg1;
        int r = 0, par = 1;
#pragma unroll 1
        for (int st = 0; st < 16; st++) {
          if ((st & 1) && st < 15) {
            const int c = (st + 1) >> 1;
            mbar_expect(bars + 8 * (B_XFULL + c), SLOT);
            tma2d(sb + c * SLOT, &maps.x, 64 * c, 128 * m1, bars + 8 * (B_XFULL + c));
          }
          mbar_wait(bars + 8 * (B_WEMPTY + r), par);
          mbar_expect(bars + 8 * (B_WFULL + r), 12288);
          tma3d_mc(sb + rank * 6144 + wslot(r) * SLOT, m0p, 0, 32 * st, 3 * f, bars + 8 * (B_WFULL + r));

          if (++r == 6) { r = 0; par ^= 1; }
        }
#pragma unroll 1
        for (int st = 0; st < 16; st++) {
          const int q4 = st & 3;
          mbar_wait(bars + 8 * (B_WEMPTY + q4), (st >> 2) & 1);
          mbar_expect(bars + 8 * (B_WFULL + q4), SLOT);
          tma3d_mc(sb + rank * 8192 + wslot(q4) * SLOT, m1p, 0, 64 * (st & 7), 24 + 2 * f + 2 * (st & 8), bars + 8 * (B_WFULL + q4));
          PROF(144 + st);
        }
      }
    } else if (warp == 13) {
      gate_rows(sb, bars, gate_w, 16 * f, 128 * m1 + 16 * f, lane);
      if (lane == 0) {
        int st = 0, par = 1;
#pragma unroll 1
        for (int c = 0; c < 28; c++) {
          if (c == 0 || c == 12 || c == 20) {
            mbar_wait(bars + 8 * (B_HRDY + (c >> 3)), 0);
            fence_proxy_async();
          }
          if (c < GRING) mbar_wait(slot_free_bar(bars, (3 * c + 2) >> 1), 0);
          else mbar_wait(bars + 8 * (B_GEMPTY + st), par);
          tma2d(sb + hoff(st), &maps.h, 64 * c, 64 * r2, bars + 8 * (B_GFULL + st));
          PROF(96 + c);
          if (++st == GRING) { st = 0; par ^= 1; }
        }
      }
    } else if (warp == 14) {
      gate_rows(sb, bars, gate_w, 16 * f + 8, 128 * m1 + 16 * f + 8, lane);
      if (lane == 0) {
        const unsigned ep = read_epoch();
        const uint32_t doff = sb + rank * 8192;
        int st = 0, par = 1;
#pragma unroll 1
        for (int c = 0; c < 28; c++) {
          if (c < GRING) { mbar_wait(slot_free_bar(bars, (3 * c) >> 1), 0); mbar_wait(slot_free_bar(bars, (3 * c + 1) >> 1), 0); }
          else mbar_wait(bars + 8 * (B_GEMPTY + st), par);
          mbar_expect(bars + 8 * (B_GFULL + st), SLOT + 8192);
          tma2d_mc(doff + doff2(st), &maps.wd, 128 * cb + 64 * rank, 64 * c, bars + 8 * (B_GFULL + st));
          if (++st == GRING) { st = 0; par ^= 1; }
        }
        const uint32_t fb = bars + 8 * B_QFULL;
        mbar_wait(bars + 8 * (B_GEMPTY + 4), 0);
        mbar_wait(bars + 8 * (B_GEMPTY + 5), 0);
        mbar_arrive(bars + 8 * B_YSLOT);
        mbar_expect(fb, SLOT + 256);
        tma2d(sb + doff2(4), &maps.xq, 128 * cb, 64 * r2, fb);
        tma2d(sb + doff2(4) + 8192, &maps.xq, 128 * cb + 64, 64 * r2, fb);
        flag_wait(C_PRE, ep * 2 * NCTA);
        fence_proxy_async();
        bulk_g2s(sb + OFF_GATE, g_gate + 64 * r2, 256, fb);
      }
    } else {
      const unsigned target = read_epoch() * 8;
      bar_sync(8, 160);
      if (lane == 0) flag_signal(C_PREU + (b & 7));
#pragma unroll 1
      for (int j = 0; j < 3; j++) {
        bar_sync(4 + j, 288);
        if (lane == 0) {
          flag_signal(C_FH + 4 * m1 + j);
          PROF(50 + j);
          flag_wait(C_FH + 4 * m2 + j, target);
          mbar_arrive(bars + 8 * (B_HRDY + j));
        }
        __syncwarp();
      }
      if (lane == 0) {
        mbar_wait(bars + 8 * (B_CDONE + 3), 0);
        PROF(54);
        flag_wait(C_CONV + cb, target * 4);
        fence_proxy_async();
        PROF(55);
        mbar_wait(bars + 8 * B_YSLOT, 0);
        mbar_expect(bars + 8 * B_YFULL, SLOT);
        tma2d(sb + doff2(5), &maps.y, 64 * r2, 128 * cb, bars + 8 * B_YFULL);
      }
    }
    __syncwarp();
    asm volatile("barrier.cluster.arrive.relaxed.aligned;\nbarrier.cluster.wait.aligned; // prod" ::: "memory");
  }
}

typedef CUresult (*EncFn)(CUtensorMap*, CUtensorMapDataType, cuuint32_t, void*, const cuuint64_t*, const cuuint64_t*,
                          const cuuint32_t*, const cuuint32_t*, CUtensorMapInterleave, CUtensorMapSwizzle,
                          CUtensorMapL2promotion, CUtensorMapFloatOOBfill);

void make2d(EncFn enc, CUtensorMap* m, const void* p, int cols, int rows, int bc, int br) {
  cuuint64_t gd[2] = {(cuuint64_t)cols, (cuuint64_t)rows};
  cuuint64_t gs[1] = {(cuuint64_t)cols * 2};
  cuuint32_t bx[2] = {(cuuint32_t)bc, (cuuint32_t)br};
  cuuint32_t es[2] = {1, 1};
  enc(m, CU_TENSOR_MAP_DATA_TYPE_BFLOAT16, 2, const_cast<void*>(p), gd, gs, bx, es, CU_TENSOR_MAP_INTERLEAVE_NONE,
      CU_TENSOR_MAP_SWIZZLE_128B, CU_TENSOR_MAP_L2_PROMOTION_L2_128B, CU_TENSOR_MAP_FLOAT_OOB_FILL_NONE);
}
void makeW(EncFn enc, CUtensorMap* m, const void* p, int bk, int ngroups) {
  cuuint64_t gd[3] = {32, (cuuint64_t)D_DIM, (cuuint64_t)(F_DIM / 32)};
  cuuint64_t gs[2] = {(cuuint64_t)F_DIM * 2, 64};
  cuuint32_t bx[3] = {32, (cuuint32_t)bk, (cuuint32_t)ngroups};
  cuuint32_t es[3] = {1, 1, 1};
  enc(m, CU_TENSOR_MAP_DATA_TYPE_BFLOAT16, 3, const_cast<void*>(p), gd, gs, bx, es, CU_TENSOR_MAP_INTERLEAVE_NONE,
      CU_TENSOR_MAP_SWIZZLE_64B, CU_TENSOR_MAP_L2_PROMOTION_L2_128B, CU_TENSOR_MAP_FLOAT_OOB_FILL_NONE);
}

}

extern "C" void kernel_launch(void* const* d_in, const int* in_sizes, int n_in, void* d_out, int out_size) {
  (void)in_sizes; (void)n_in; (void)out_size;
  const __nv_bfloat16* q = (const __nv_bfloat16*)d_in[0];
  const __nv_bfloat16* k = (const __nv_bfloat16*)d_in[1];
  const __nv_bfloat16* v = (const __nv_bfloat16*)d_in[2];
  const __nv_bfloat16* shift_k = (const __nv_bfloat16*)d_in[3];
  const __nv_bfloat16* ssm_k = (const __nv_bfloat16*)d_in[4];
  const __nv_bfloat16* ssm_D = (const __nv_bfloat16*)d_in[5];
  const __nv_bfloat16* w_gate = (const __nv_bfloat16*)d_in[7];
  const __nv_bfloat16* w_up = (const __nv_bfloat16*)d_in[8];
  const __nv_bfloat16* w_down = (const __nv_bfloat16*)d_in[9];
  const __nv_bfloat16* gate_w = (const __nv_bfloat16*)d_in[10];

  static EncFn enc = nullptr;
  static void* pH = nullptr;
  static void* pY = nullptr;
  if (!enc) {
    cudaDriverEntryPointQueryResult qr;
    cudaGetDriverEntryPoint("cuTensorMapEncodeTiled", (void**)&enc, cudaEnableDefault, &qr);
    cudaGetSymbolAddress(&pH, g_H);
    cudaGetSymbolAddress(&pY, g_yT);
    cudaFuncSetAttribute(fused_kernel, cudaFuncAttributeMaxDynamicSharedMemorySize, SMEM_BYTES);
  }
  Maps maps;
  make2d(enc, &maps.x, q, D_DIM, S_LEN, 64, 128);
  makeW(enc, &maps.wg0, w_gate, 32, 3);
  makeW(enc, &maps.wu0, w_up, 32, 3);
  makeW(enc, &maps.wg1, w_gate, 64, 2);
  makeW(enc, &maps.wu1, w_up, 64, 2);
  make2d(enc, &maps.h, pH, F_DIM, S_LEN, 64, 64);
  make2d(enc, &maps.wd, w_down, D_DIM, F_DIM, 64, 64);
  make2d(enc, &maps.y, pY, S_LEN, D_DIM, 64, 128);
  make2d(enc, &maps.xq, q, D_DIM, S_LEN, 64, 64);
  fused_kernel<<<NCTA, NTHREADS, SMEM_BYTES>>>(maps, q, k, v, shift_k, ssm_k, ssm_D, gate_w, (__nv_bfloat16*)d_out);
}
```
